```python
import torch

def _softmax(x, axis=-1):
    return torch.softmax(x, dim=axis)
def _gelu(x):
    return torch.nn.functional.gelu(x, approximate="tanh")
def _silu(x):
    return torch.nn.functional.silu(x)
def _sigmoid(x):
    return torch.sigmoid(x)
def _layernorm(x, axis=-1, eps=1e-5):
    m = x.mean(dim=axis, keepdim=True)
    v = x.var(dim=axis, keepdim=True, unbiased=False)
    return (x - m) / torch.sqrt(v + eps)
def _scatter_add(tgt, idx, src, axis=0):
    return tgt.clone().index_add_(axis, idx, src)
def _segment_sum(src, seg, n):
    out = torch.zeros((n,) + src.shape[1:], dtype=src.dtype)
    return out.index_add_(0, seg, src)
def _pad(x, pw):
    flat = tuple(v for pair in reversed(pw) for v in pair)
    return torch.nn.functional.pad(x, flat)

kernel_name = 'standalone__window_attn_swin_v2__vision'

def setup_inputs():

    _w = (lambda a: (lambda t: t.to(torch.bfloat16) if t.is_floating_point() else t)(torch.as_tensor(a)))
    win = 8
    H = W = (384 // win) * win
    C = 96
    nh = 4
    shift = win // 2
    coords = torch.stack(torch.meshgrid(torch.arange(win), torch.arange(win), indexing="ij"), -1).reshape(-1, 2)
    rel = coords[:, None, :] - coords[None, :, :]
    rel_idx = ((rel[..., 0] + win - 1) * (2 * win - 1) + (rel[..., 1] + win - 1)).to(torch.int64)
    tab = torch.stack(torch.meshgrid(torch.arange(1 - win, win), torch.arange(1 - win, win), indexing="ij"), -1).reshape(-1, 2).to(float)
    tab = (lambda _x: torch.sign(torch.as_tensor(_x)))(tab) * (lambda _x: torch.log1p(torch.as_tensor(_x)))(torch.abs(tab))
    img = torch.zeros((H, W), dtype=torch.int64)
    cnt = 0
    for hs in (slice(0, H - win), slice(H - win, H - shift), slice(H - shift, H)):
        for ws in (slice(0, W - win), slice(W - win, W - shift), slice(W - shift, W)):
            img[hs, ws] = cnt; cnt += 1
    mw = img.reshape(H // win, win, W // win, win).permute(0, 2, 1, 3).reshape(-1, win * win)
    mask = (mw[:, :, None] != mw[:, None, :]).to(float) * (-100.0)
    return {
        "x": _w((lambda *s: torch.randn(*s, dtype=torch.bfloat16) * 0.05)(1, H, W, C)),
        "wqkv": _w((lambda *s: torch.randn(*s, dtype=torch.bfloat16) * 1.6)(C, 3 * C)),
        "wo": _w((lambda *s: torch.randn(*s, dtype=torch.bfloat16) * 0.05)(C, C)),
        "logit_scale": _w((lambda *s: torch.randn(*s, dtype=torch.bfloat16) * 1.6)(nh)),
        "cpb_w1": _w((lambda *s: torch.randn(*s, dtype=torch.bfloat16) * 0.8)(2, 4 * nh)),
        "cpb_w2": _w((lambda *s: torch.randn(*s, dtype=torch.bfloat16) * 0.8)(4 * nh, nh)),
        "rel_coords": _w(tab),
        "rel_idx": _w(rel_idx),
        "attn_mask": _w(mask),
    }

def reference(x, wqkv, wo, logit_scale, cpb_w1, cpb_w2, rel_coords, rel_idx, attn_mask):
    B, H, W, C = x.shape
    win = 8
    nh = 4
    hd = C // nh
    shift = win // 2
    ww = win * win
    nH, nW = H // win, W // win
    xs = torch.roll(x, (-shift, -shift), (1, 2))
    xw = (lambda x, *d: x.permute(*d))(xs.reshape(B, nH, win, nW, win, C), 0, 1, 3, 2, 4, 5).reshape(B * nH * nW, ww, C)
    qkv = (lambda x, *d: x.permute(*d))((xw @ wqkv).reshape(B * nH * nW, ww, 3, nh, hd), 2, 0, 3, 1, 4)
    q, k, v = qkv[0], qkv[1], qkv[2]
    qn = q * (torch.einsum("bhqd,bhqd->bhq", q, q)[..., None] + 1e-12) ** -0.5
    kn = k * (torch.einsum("bhkd,bhkd->bhk", k, k)[..., None] + 1e-12) ** -0.5
    logits = torch.einsum("bhqd,bhkd->bhqk", qn, kn)
    tau = torch.exp(torch.clip(logit_scale, -100.0, 4.6052))
    logits = logits * tau[None, :, None, None]
    hcpb = rel_coords @ cpb_w1
    hcpb = torch.where(hcpb > 0, hcpb, hcpb * 0)
    bias_tab = 16.0 * _sigmoid(hcpb @ cpb_w2)
    bias = (lambda x, *d: x.permute(*d))(bias_tab[rel_idx], 2, 0, 1)
    logits = logits.reshape(B, nH * nW, nh, ww, ww) + bias[None, None, :, :, :] + attn_mask[None, :, None, :, :]
    p = _softmax(logits.reshape(B * nH * nW, nh, ww, ww), axis=-1)
    o = (lambda x, *d: x.permute(*d))(torch.einsum("bhqk,bhkd->bhqd", p, v), 0, 2, 1, 3).reshape(B * nH * nW, ww, C) @ wo
    o = (lambda x, *d: x.permute(*d))(o.reshape(B, nH, nW, win, win, C), 0, 1, 3, 2, 4, 5).reshape(B, H, W, C)
    o = torch.roll(o, (shift, shift), (1, 2))
    return _layernorm(o, axis=-1)
```

```cpp
#include <cuda_runtime.h>
#include <cuda_bf16.h>
#include <cuda_fp16.h>
#include <stdint.h>

namespace {

constexpr int NWG      = 4;
constexpr int NTHREADS = NWG * 128;
constexpr int IMG      = 384;
constexpr int WSIDE    = 48;
constexpr int NWIN     = WSIDE * WSIDE;
constexpr int NTAB     = 225;
constexpr float LOG2E  = 1.4426950408889634f;

constexpr int OFF_ZLO  = 0;
constexpr int OFF_WQKV = 1024;
constexpr int WQKV_LBO = 36 * 128;
constexpr int OFF_WO   = OFF_WQKV + 12 * WQKV_LBO;
constexpr int WO_LBO   = 12 * 128;
constexpr int OFF_BIAS = OFF_WO + 12 * WO_LBO;
constexpr int OFF_KV   = OFF_BIAS + 32768;
constexpr int HEAD_STRIDE = 7 * 1024 + 32;
constexpr int KV_STRIDE   = 4 * HEAD_STRIDE;
constexpr int OFF_ZHI  = OFF_KV + NWG * KV_STRIDE;
constexpr int OFF_TAB  = OFF_ZHI + 1024;
constexpr int SMEM_BYTES = OFF_TAB + 2048;

__device__ __forceinline__ uint64_t make_desc(uint32_t addr, uint32_t lbo, uint32_t sbo) {
    return (uint64_t)((addr & 0x3FFFF) >> 4) | ((uint64_t)(lbo >> 4) << 16) | ((uint64_t)(sbo >> 4) << 32);
}
__device__ __forceinline__ void wg_fence()  { asm volatile("wgmma.fence.sync.aligned;" ::: "memory"); }
__device__ __forceinline__ void wg_commit() { asm volatile("wgmma.commit_group.sync.aligned;" ::: "memory"); }
template <int N> __device__ __forceinline__ void wg_wait() {
    asm volatile("wgmma.wait_group.sync.aligned %0;" ::"n"(N) : "memory");
}
template <int N> __device__ __forceinline__ void pin(float (&d)[N]) {
#pragma unroll
    for (int i = 0; i < N; i++) asm volatile("" : "+f"(d[i])::"memory");
}
template <int N> __device__ __forceinline__ void pin(uint32_t (&d)[N]) {
#pragma unroll
    for (int i = 0; i < N; i++) asm volatile("" : "+r"(d[i])::"memory");
}

#define F8(C, d, o) C(d[o + 0]), C(d[o + 1]), C(d[o + 2]), C(d[o + 3]), C(d[o + 4]), C(d[o + 5]), C(d[o + 6]), C(d[o + 7])
#define RW_F(x) "+f"(x)
#define WO_F(x) "=f"(x)
#define RW_R(x) "+r"(x)

#define N96_REGS                                                                                  \
    "{%0,%1,%2,%3,%4,%5,%6,%7,%8,%9,%10,%11,%12,%13,%14,%15,%16,%17,%18,%19,%20,%21,%22,%23,"     \
    "%24,%25,%26,%27,%28,%29,%30,%31,%32,%33,%34,%35,%36,%37,%38,%39,%40,%41,%42,%43,%44,%45,%46,%47}"

template <bool FIRST>
__device__ __forceinline__ void mma_n96(float (&d)[48], uint32_t a0, uint32_t a1, uint32_t a2, uint32_t a3, uint64_t db) {
    if (FIRST) {
        asm volatile("wgmma.mma_async.sync.aligned.m64n96k16.f32.bf16.bf16 " N96_REGS
                     ", {%48,%49,%50,%51}, %52, 0, 1, 1, 1;"
                     : F8(WO_F, d, 0), F8(WO_F, d, 8), F8(WO_F, d, 16), F8(WO_F, d, 24), F8(WO_F, d, 32), F8(WO_F, d, 40)
                     : "r"(a0), "r"(a1), "r"(a2), "r"(a3), "l"(db));
    } else {
        asm volatile("wgmma.mma_async.sync.aligned.m64n96k16.f32.bf16.bf16 " N96_REGS
                     ", {%48,%49,%50,%51}, %52, 1, 1, 1, 1;"
                     : F8(RW_F, d, 0), F8(RW_F, d, 8), F8(RW_F, d, 16), F8(RW_F, d, 24), F8(RW_F, d, 32), F8(RW_F, d, 40)
                     : "r"(a0), "r"(a1), "r"(a2), "r"(a3), "l"(db));
    }
}
#define N16_REGS "{%0,%1,%2,%3,%4,%5,%6,%7,%8,%9,%10,%11,%12,%13,%14,%15}"
__device__ __forceinline__ void mma_qk(uint32_t (&d)[16], uint32_t a0, uint32_t a1, uint32_t a2, uint32_t a3, uint64_t db) {
    asm volatile("wgmma.mma_async.sync.aligned.m64n64k16.f16.f16.f16 " N16_REGS
                 ", {%16,%17,%18,%19}, %20, 1, 1, 1, 0;"
                 : F8(RW_R, d, 0), F8(RW_R, d, 8)
                 : "r"(a0), "r"(a1), "r"(a2), "r"(a3), "l"(db));
}
template <bool FIRST>
__device__ __forceinline__ void mma_pv(float (&d)[16], uint32_t a0, uint32_t a1, uint32_t a2, uint32_t a3, uint64_t db) {
    if (FIRST) {
        asm volatile("wgmma.mma_async.sync.aligned.m64n32k16.f32.f16.f16 " N16_REGS
                     ", {%16,%17,%18,%19}, %20, 0, 1, 1, 1;"
                     : F8(WO_F, d, 0), F8(WO_F, d, 8)
                     : "r"(a0), "r"(a1), "r"(a2), "r"(a3), "l"(db));
    } else {
        asm volatile("wgmma.mma_async.sync.aligned.m64n32k16.f32.f16.f16 " N16_REGS
                     ", {%16,%17,%18,%19}, %20, 1, 1, 1, 1;"
                     : F8(RW_F, d, 0), F8(RW_F, d, 8)
                     : "r"(a0), "r"(a1), "r"(a2), "r"(a3), "l"(db));
    }
}

__device__ __forceinline__ uint32_t pack_f16(float lo, float hi) {
    uint32_t r; asm("cvt.rn.f16x2.f32 %0, %1, %2;" : "=r"(r) : "f"(hi), "f"(lo)); return r;
}
__device__ __forceinline__ uint32_t pack_f16_sat(float lo, float hi) {
    uint32_t r; asm("cvt.rn.satfinite.f16x2.f32 %0, %1, %2;" : "=r"(r) : "f"(hi), "f"(lo)); return r;
}
__device__ __forceinline__ uint32_t pack_bf16(float lo, float hi) {
    uint32_t r; asm("cvt.rn.bf16x2.f32 %0, %1, %2;" : "=r"(r) : "f"(hi), "f"(lo)); return r;
}
__device__ __forceinline__ float bf_lo(uint32_t v) { return __uint_as_float(v << 16); }
__device__ __forceinline__ float bf_hi(uint32_t v) { return __uint_as_float(v & 0xFFFF0000u); }
__device__ __forceinline__ float bf_round(float x) { return __bfloat162float(__float2bfloat16_rn(x)); }
__device__ __forceinline__ __half2 as_h2(uint32_t v) { return *reinterpret_cast<__half2*>(&v); }
__device__ __forceinline__ uint32_t as_u32(__half2 v) { return *reinterpret_cast<uint32_t*>(&v); }
__device__ __forceinline__ uint32_t ex2_h2(uint32_t v) {
    uint32_t r; asm("ex2.approx.f16x2 %0, %1;" : "=r"(r) : "r"(v)); return r;
}
__device__ __forceinline__ float rsqrt_fast(float x) {
    float r; asm("rsqrt.approx.ftz.f32 %0, %1;" : "=f"(r) : "f"(x)); return r;
}
__device__ __forceinline__ float rcp_fast(float x) {
    float r; asm("rcp.approx.ftz.f32 %0, %1;" : "=f"(r) : "f"(x)); return r;
}
__device__ __forceinline__ void ldg_stream(uint32_t* r, const void* p) {
    asm volatile("ld.global.nc.L1::no_allocate.v4.u32 {%0,%1,%2,%3}, [%4];"
                 : "=r"(r[0]), "=r"(r[1]), "=r"(r[2]), "=r"(r[3]) : "l"(p));
}
__device__ __forceinline__ void sts128(uint32_t addr, uint32_t a, uint32_t b, uint32_t c, uint32_t d) {
    asm volatile("st.shared.v4.u32 [%0], {%1,%2,%3,%4};" ::"r"(addr), "r"(a), "r"(b), "r"(c), "r"(d) : "memory");
}
__device__ __forceinline__ void lds128(uint32_t* r, uint32_t addr) {
    asm volatile("ld.shared.v4.u32 {%0,%1,%2,%3}, [%4];" : "=r"(r[0]), "=r"(r[1]), "=r"(r[2]), "=r"(r[3]) : "r"(addr));
}
__device__ __forceinline__ void bar_wg(int id) { asm volatile("bar.sync %0, 128;" ::"r"(id) : "memory"); }

__device__ __forceinline__ void token_offsets(int win, int w, int g, int c, uint32_t& offA, uint32_t& offB) {
    int wy = win / WSIDE, wx = win - wy * WSIDE;
    int y = wy * 8 + 4 + 2 * w;
    int x = wx * 8 + 4 + g;
    if (y >= IMG) y -= IMG;
    if (x >= IMG) x -= IMG;
    offA = (uint32_t)(y * IMG + x) * 192u + 16u * c;
    offB = offA + IMG * 192u;
}

#define XI(s) (4 * ((s) >> 1) + ((s) & 1))
#define XF(s) xr[XI(s)], xr[12 + XI(s)], xr[XI(s) + 2], xr[12 + XI(s) + 2]

__global__ void __launch_bounds__(NTHREADS, 1)
swin_attn_kernel(const __nv_bfloat16* __restrict__ x, const __nv_bfloat16* __restrict__ wqkv,
                 const __nv_bfloat16* __restrict__ wo, const __nv_bfloat16* __restrict__ logit_scale,
                 const __nv_bfloat16* __restrict__ cpb_w1, const __nv_bfloat16* __restrict__ cpb_w2,
                 const __nv_bfloat16* __restrict__ rel_coords, const int* __restrict__ rel_idx,
                 const __nv_bfloat16* __restrict__ mask, __nv_bfloat16* __restrict__ out) {
    extern __shared__ __align__(1024) uint8_t smem[];
    const uint32_t sbase = (uint32_t)__cvta_generic_to_shared(smem);
    const int tid  = threadIdx.x;
    const int lane = tid & 31;
    const int wg   = __shfl_sync(0xffffffffu, tid >> 7, 0);
    const int w    = __shfl_sync(0xffffffffu, (tid >> 5) & 3, 0);
    const int g = lane >> 2, c = lane & 3;
    const int wstride = gridDim.x * NWG;
    int win = wg * gridDim.x + blockIdx.x;

    const char* xb = reinterpret_cast<const char*>(x);
    char* ob = reinterpret_cast<char*>(out);
    const char* mb = reinterpret_cast<const char*>(mask) + (16 * w + g) * 128 + 16 * c;

    uint32_t xr[24];
    uint32_t offA = 0, offB = 0;
    if (win < NWIN) {
        token_offsets(win, w, g, c, offA, offB);
#pragma unroll
        for (int j = 0; j < 3; j++) { ldg_stream(&xr[4 * j], xb + offA + 64 * j); ldg_stream(&xr[12 + 4 * j], xb + offB + 64 * j); }
    }

    {
        auto chan = [](int kk) { int s = kk >> 4, hh = (kk >> 3) & 1, cc = (kk >> 1) & 3, e = kk & 1;
                                 return 32 * (s >> 1) + 8 * cc + 2 * (s & 1) + 4 * hh + e; };
        for (int task = tid; task < 96 * 6; task += NTHREADS) {
            int k8 = task & 7, rest = task >> 3;
            int pj = rest % 6, kg = rest / 6;
            int part = pj / 3, j = pj - 3 * part;
            int kk = kg * 8 + k8;
            const uint4* src = reinterpret_cast<const uint4*>(wqkv + chan(kk) * 288 + 96 + 96 * part + 8 * j);
            uint4 v0 = __ldg(src), v1 = __ldg(src + 3), v2 = __ldg(src + 6), v3 = __ldg(src + 9);
            uint32_t dst = sbase + OFF_WQKV + kg * WQKV_LBO + (part * 12 + 4 * j) * 128 + k8 * 16;
            sts128(dst,       v0.x, v1.x, v2.x, v3.x);
            sts128(dst + 128, v0.y, v1.y, v2.y, v3.y);
            sts128(dst + 256, v0.z, v1.z, v2.z, v3.z);
            sts128(dst + 384, v0.w, v1.w, v2.w, v3.w);
        }
        for (int task = tid; task < 96 * 12; task += NTHREADS) {
            int k8 = task & 7, rest = task >> 3;
            int ng = rest % 12, kg = rest / 12;
            int kk = kg * 8 + k8;
            uint4 v = __ldg(reinterpret_cast<const uint4*>(wqkv + chan(kk) * 288 + 8 * ng));
            sts128(sbase + OFF_WQKV + kg * WQKV_LBO + (24 + ng) * 128 + k8 * 16, v.x, v.y, v.z, v.w);
        }
        if (tid < 384) {
            int k = tid >> 2;
            uint32_t v[12];
#pragma unroll
            for (int j = 0; j < 3; j++) {
                uint4 t4 = __ldg(reinterpret_cast<const uint4*>(wo + k * 96 + 32 * j + 8 * c));
                v[4 * j] = t4.x; v[4 * j + 1] = t4.y; v[4 * j + 2] = t4.z; v[4 * j + 3] = t4.w;
            }
            float s = 0.f;
#pragma unroll
            for (int i = 0; i < 12; i++) s += bf_lo(v[i]) + bf_hi(v[i]);
            s += __shfl_xor_sync(0xffffffffu, s, 1);
            s += __shfl_xor_sync(0xffffffffu, s, 2);
            float mean = s * (1.0f / 96.0f);
            uint32_t dst = sbase + OFF_WO + (k >> 3) * WO_LBO + (k & 7) * 16 + 4 * c;
#pragma unroll
            for (int i = 0; i < 12; i++) {
                uint32_t p = pack_bf16(bf_lo(v[i]) - mean, bf_hi(v[i]) - mean);
                asm volatile("st.shared.u32 [%0], %1;" ::"r"(dst + i * 128), "r"(p) : "memory");
            }
        }
        if (tid < NTAB) {
            float r0 = __bfloat162float(rel_coords[2 * tid]), r1 = __bfloat162float(rel_coords[2 * tid + 1]);
            float z[4] = {0.f, 0.f, 0.f, 0.f};
#pragma unroll
            for (int j = 0; j < 16; j++) {
                float hc = bf_round(r0 * __bfloat162float(cpb_w1[j]) + r1 * __bfloat162float(cpb_w1[16 + j]));
                hc = hc > 0.f ? hc : hc * 0.f;
#pragma unroll
                for (int h = 0; h < 4; h++) z[h] += hc * __bfloat162float(cpb_w2[4 * j + h]);
            }
            float b[4];
#pragma unroll
            for (int h = 0; h < 4; h++) {
                float zz = bf_round(z[h]);
                b[h] = 16.0f * bf_round(1.0f / (1.0f + __expf(-zz))) * LOG2E;
            }
            asm volatile("st.shared.v2.u32 [%0], {%1,%2};" ::"r"(sbase + OFF_TAB + tid * 8),
                         "r"(pack_f16(b[0], b[1])), "r"(pack_f16(b[2], b[3])) : "memory");
        }
        {
            int t = tid & 127;
#pragma unroll
            for (int i = 0; i < 2; i++) {
                int idx = t + 128 * i;
                sts128(sbase + OFF_KV + wg * KV_STRIDE + (idx >> 6) * HEAD_STRIDE + 3 * 1024 + (idx & 63) * 16,
                       0x3C003C00u, 0x3C003C00u, 0x3C003C00u, 0x3C003C00u);
            }
        }
        if (tid < 128) sts128(sbase + (tid < 64 ? OFF_ZLO : OFF_ZHI - 1024) + tid * 16, 0u, 0u, 0u, 0u);
        int4 ia, ib;
        const int bw = (tid >> 7) & 3, bq = (tid >> 5) & 3;
        if (tid < 512) {
            const int* p = rel_idx + (16 * bw + g) * 64 + 32 * (bq >> 1) + 8 * c + 4 * (bq & 1);
            ia = __ldg(reinterpret_cast<const int4*>(p));
            ib = __ldg(reinterpret_cast<const int4*>(p + 8 * 64));
        }
        __syncthreads();
        if (tid < 512) {
            int id[8] = {ia.x, ia.y, ib.x, ib.y, ia.z, ia.w, ib.z, ib.w};
            uint2 e[8];
#pragma unroll
            for (int i = 0; i < 8; i++) {
                unsigned u = min((unsigned)id[i], (unsigned)(NTAB - 1));
                e[i] = *reinterpret_cast<const uint2*>(smem + OFF_TAB + u * 8);
            }
            uint32_t dst = sbase + OFF_BIAS + (bw * 4 + bq) * 512 + lane * 16;
            sts128(dst,         __byte_perm(e[0].x, e[1].x, 0x5410), __byte_perm(e[2].x, e[3].x, 0x5410),
                                __byte_perm(e[4].x, e[5].x, 0x5410), __byte_perm(e[6].x, e[7].x, 0x5410));
            sts128(dst + 8192,  __byte_perm(e[0].x, e[1].x, 0x7632), __byte_perm(e[2].x, e[3].x, 0x7632),
                                __byte_perm(e[4].x, e[5].x, 0x7632), __byte_perm(e[6].x, e[7].x, 0x7632));
            sts128(dst + 16384, __byte_perm(e[0].y, e[1].y, 0x5410), __byte_perm(e[2].y, e[3].y, 0x5410),
                                __byte_perm(e[4].y, e[5].y, 0x5410), __byte_perm(e[6].y, e[7].y, 0x5410));
            sts128(dst + 24576, __byte_perm(e[0].y, e[1].y, 0x7632), __byte_perm(e[2].y, e[3].y, 0x7632),
                                __byte_perm(e[4].y, e[5].y, 0x7632), __byte_perm(e[6].y, e[7].y, 0x7632));
        }
        asm volatile("fence.proxy.async.shared::cta;" ::: "memory");
        __syncthreads();
    }
    float qscale[4];
#pragma unroll
    for (int h = 0; h < 4; h++) {
        float ls = bf_round(fminf(fmaxf(__bfloat162float(logit_scale[h]), -100.0f), 4.6052f));
        qscale[h] = bf_round(expf(ls)) * LOG2E;
    }

    const uint32_t kv = sbase + OFF_KV + wg * KV_STRIDE;
    const uint32_t st_kv = kv + c * HEAD_STRIDE + (32 * (w >> 1) + 8 * (g >> 1) + 4 * (w & 1) + (g & 1)) * 16;
    const uint32_t ld_bias = sbase + OFF_BIAS + w * 2048 + lane * 16;
    const uint64_t d_wqkv = make_desc(sbase + OFF_WQKV, WQKV_LBO, 128);
    const uint64_t d_wo   = make_desc(sbase + OFF_WO, WO_LBO, 128);
    const uint64_t d_v    = make_desc(kv, 128, 1024);

    for (; win < NWIN; win += wstride) {
        uint32_t mr[16];
        {
            const char* mp = mb + (size_t)win * 8192;
            ldg_stream(&mr[0], mp); ldg_stream(&mr[4], mp + 64);
            ldg_stream(&mr[8], mp + 1024); ldg_stream(&mr[12], mp + 1024 + 64);
        }
        float acc[48];
        wg_fence();
#pragma unroll
        for (int s = 0; s < 6; s++) {
            uint64_t db = d_wqkv + (uint64_t)((s * 2 * WQKV_LBO) >> 4);
            if (s == 0) mma_n96<true>(acc, XF(s), db);
            else        mma_n96<false>(acc, XF(s), db);
        }
        wg_commit();
        wg_wait<0>();
        pin(acc);
        {
            float a0 = 0.f, a1 = 0.f, b0 = 0.f, b1 = 0.f;
#pragma unroll
            for (int t = 0; t < 12; t++) {
                a0 = fmaf(acc[4 * t], acc[4 * t], a0);         a1 = fmaf(acc[4 * t + 1], acc[4 * t + 1], a1);
                b0 = fmaf(acc[4 * t + 2], acc[4 * t + 2], b0); b1 = fmaf(acc[4 * t + 3], acc[4 * t + 3], b1);
            }
            float ra = rsqrt_fast(a0 + a1 + 1e-12f), rb = rsqrt_fast(b0 + b1 + 1e-12f);
            bar_wg(1 + wg);
#pragma unroll
            for (int j = 0; j < 3; j++) {
                const float* a = &acc[16 * j];
                sts128(st_kv + (4 + j) * 1024, pack_f16(a[0] * ra, a[1] * ra), pack_f16(a[4] * ra, a[5] * ra),
                       pack_f16(a[8] * ra, a[9] * ra), pack_f16(a[12] * ra, a[13] * ra));
                sts128(st_kv + (4 + j) * 1024 + 32, pack_f16(a[2] * rb, a[3] * rb), pack_f16(a[6] * rb, a[7] * rb),
                       pack_f16(a[10] * rb, a[11] * rb), pack_f16(a[14] * rb, a[15] * rb));
            }
        }
        wg_fence();
#pragma unroll
        for (int s = 0; s < 6; s++) {
            uint64_t db = d_wqkv + (uint64_t)((s * 2 * WQKV_LBO + 12 * 128) >> 4);
            if (s == 0) mma_n96<true>(acc, XF(s), db);
            else        mma_n96<false>(acc, XF(s), db);
        }
        wg_commit();
        wg_wait<0>();
        pin(acc);
#pragma unroll
        for (int j = 0; j < 3; j++) {
            const float* a = &acc[16 * j];
            sts128(st_kv + j * 1024, pack_f16_sat(a[0], a[1]), pack_f16_sat(a[4], a[5]), pack_f16_sat(a[8], a[9]), pack_f16_sat(a[12], a[13]));
            sts128(st_kv + j * 1024 + 32, pack_f16_sat(a[2], a[3]), pack_f16_sat(a[6], a[7]), pack_f16_sat(a[10], a[11]), pack_f16_sat(a[14], a[15]));
        }
        asm volatile("fence.proxy.async.shared::cta;" ::: "memory");
        wg_fence();
#pragma unroll
        for (int s = 0; s < 6; s++) {
            uint64_t db = d_wqkv + (uint64_t)((s * 2 * WQKV_LBO + 24 * 128) >> 4);
            if (s == 0) mma_n96<true>(acc, XF(s), db);
            else        mma_n96<false>(acc, XF(s), db);
        }
        wg_commit();
        bar_wg(1 + wg);
        bool has_mask;
        {
            uint32_t any = 0;
#pragma unroll
            for (int i = 0; i < 16; i++) any |= mr[i];
            has_mask = __any_sync(0xffffffffu, (any & 0x7FFF7FFFu) != 0);
        }
        wg_wait<0>();
        pin(acc);
        uint32_t qf[24];
#pragma unroll
        for (int h = 0; h < 4; h++) {
            const float* a = &acc[12 * h];
            float sa = a[0] * a[0], sb = a[2] * a[2];
            sa = fmaf(a[1], a[1], sa); sb = fmaf(a[3], a[3], sb);
            sa = fmaf(a[4], a[4], sa); sb = fmaf(a[6], a[6], sb);
            sa = fmaf(a[5], a[5], sa); sb = fmaf(a[7], a[7], sb);
            sa = fmaf(a[8], a[8], sa); sb = fmaf(a[10], a[10], sb);
            sa = fmaf(a[9], a[9], sa); sb = fmaf(a[11], a[11], sb);
            sa += __shfl_xor_sync(0xffffffffu, sa, 1); sb += __shfl_xor_sync(0xffffffffu, sb, 1);
            sa += __shfl_xor_sync(0xffffffffu, sa, 2); sb += __shfl_xor_sync(0xffffffffu, sb, 2);
            float ra = rsqrt_fast(sa + 1e-12f) * qscale[h], rb = rsqrt_fast(sb + 1e-12f) * qscale[h];
#pragma unroll
            for (int j = 0; j < 3; j++) {
                qf[6 * h + 2 * j]     = pack_f16(a[4 * j] * ra, a[4 * j + 1] * ra);
                qf[6 * h + 2 * j + 1] = pack_f16(a[4 * j + 2] * rb, a[4 * j + 3] * rb);
            }
        }
        uint32_t sacc[4][16];
#pragma unroll
        for (int h = 0; h < 4; h++)
#pragma unroll
            for (int q = 0; q < 4; q++) lds128(&sacc[h][4 * q], ld_bias + h * 8192 + q * 512);
        {
            if (has_mask) {
                const char* mp = mb + (size_t)win * 8192;
                ldg_stream(&mr[0], mp); ldg_stream(&mr[4], mp + 64);
                ldg_stream(&mr[8], mp + 1024); ldg_stream(&mr[12], mp + 1024 + 64);
#pragma unroll
                for (int t = 0; t < 8; t++) {
                    __half2 ma  = as_h2(pack_f16_sat(bf_lo(mr[t]) * LOG2E, bf_hi(mr[t]) * LOG2E));
                    __half2 mb2 = as_h2(pack_f16_sat(bf_lo(mr[8 + t]) * LOG2E, bf_hi(mr[8 + t]) * LOG2E));
#pragma unroll
                    for (int h = 0; h < 4; h++) {
                        sacc[h][2 * t]     = as_u32(__hadd2(as_h2(sacc[h][2 * t]), ma));
                        sacc[h][2 * t + 1] = as_u32(__hadd2(as_h2(sacc[h][2 * t + 1]), mb2));
                    }
                }
            }
        }
        wg_fence();
#pragma unroll
        for (int hp = 0; hp < 2; hp++) {
            const uint32_t* q = &qf[12 * hp];
            const uint32_t k0 = kv + 4 * 1024 + 2 * hp * HEAD_STRIDE, k1 = k0 + HEAD_STRIDE;
            mma_qk(sacc[2 * hp], q[0], q[1], q[2], q[3], make_desc(k0, 1024, 128));
            mma_qk(sacc[2 * hp], q[4], q[5], q[6], q[7], make_desc(k0 + 2048, sbase + OFF_ZHI - (k0 + 2048), 128));
            mma_qk(sacc[2 * hp + 1], q[4], q[5], q[6], q[7], make_desc(sbase + OFF_ZLO, k1 - (sbase + OFF_ZLO), 128));
            mma_qk(sacc[2 * hp + 1], q[8], q[9], q[10], q[11], make_desc(k1 + 1024, 1024, 128));
        }
        wg_commit();
        wg_wait<0>();
        pin(sacc[0]); pin(sacc[1]); pin(sacc[2]); pin(sacc[3]);

        uint32_t of[24];
        const uint32_t curA = offA, curB = offB;
#pragma unroll
        for (int h = 0; h < 4; h++) {
            uint32_t* s = sacc[h];
            __half2 ma = as_h2(s[0]), mb2 = as_h2(s[1]);
#pragma unroll
            for (int t = 1; t < 8; t++) { ma = __hmax2(ma, as_h2(s[2 * t])); mb2 = __hmax2(mb2, as_h2(s[2 * t + 1])); }
            __half2 m = __hmax2(__lows2half2(ma, mb2), __highs2half2(ma, mb2));
            m = __hmax2(m, as_h2(__shfl_xor_sync(0xffffffffu, as_u32(m), 1)));
            m = __hmax2(m, as_h2(__shfl_xor_sync(0xffffffffu, as_u32(m), 2)));
            __half2 mA = __low2half2(m), mB = __high2half2(m);
#pragma unroll
            for (int t = 0; t < 8; t++) {
                s[2 * t]     = ex2_h2(as_u32(__hsub2(as_h2(s[2 * t]), mA)));
                s[2 * t + 1] = ex2_h2(as_u32(__hsub2(as_h2(s[2 * t + 1]), mB)));
            }
            float o[16];
            wg_fence();
#pragma unroll
            for (int ks = 0; ks < 4; ks++) {
                uint64_t db = d_v + (uint64_t)((h * HEAD_STRIDE + ks * 256) >> 4);
                if (ks == 0) mma_pv<true>(o, s[0], s[1], s[2], s[3], db);
                else         mma_pv<false>(o, s[4 * ks], s[4 * ks + 1], s[4 * ks + 2], s[4 * ks + 3], db);
            }
            wg_commit();
            wg_wait<0>();
            pin(o);
            float ia = rcp_fast(o[12]), ib = rcp_fast(o[14]);
#pragma unroll
            for (int j = 0; j < 3; j++) {
                of[6 * h + 2 * j]     = pack_bf16(o[4 * j] * ia, o[4 * j + 1] * ia);
                of[6 * h + 2 * j + 1] = pack_bf16(o[4 * j + 2] * ib, o[4 * j + 3] * ib);
            }
            if (h == 1) {
                int nxt = win + wstride;
                if (nxt < NWIN) {
                    token_offsets(nxt, w, g, c, offA, offB);
#pragma unroll
                    for (int j = 0; j < 3; j++) { ldg_stream(&xr[4 * j], xb + offA + 64 * j); ldg_stream(&xr[12 + 4 * j], xb + offB + 64 * j); }
                }
            }
        }
        wg_fence();
#pragma unroll
        for (int s = 0; s < 6; s++) {
            uint64_t db = d_wo + (uint64_t)((s * 2 * WO_LBO) >> 4);
            if (s == 0) mma_n96<true>(acc, of[4 * s], of[4 * s + 1], of[4 * s + 2], of[4 * s + 3], db);
            else        mma_n96<false>(acc, of[4 * s], of[4 * s + 1], of[4 * s + 2], of[4 * s + 3], db);
        }
        wg_commit();
        wg_wait<0>();
        pin(acc);
        {
            float a0 = 0.f, a1 = 0.f, b0 = 0.f, b1 = 0.f;
#pragma unroll
            for (int t = 0; t < 12; t++) {
                a0 = fmaf(acc[4 * t], acc[4 * t], a0);         a1 = fmaf(acc[4 * t + 1], acc[4 * t + 1], a1);
                b0 = fmaf(acc[4 * t + 2], acc[4 * t + 2], b0); b1 = fmaf(acc[4 * t + 3], acc[4 * t + 3], b1);
            }
            a0 += a1; b0 += b1;
            a0 += __shfl_xor_sync(0xffffffffu, a0, 1); b0 += __shfl_xor_sync(0xffffffffu, b0, 1);
            a0 += __shfl_xor_sync(0xffffffffu, a0, 2); b0 += __shfl_xor_sync(0xffffffffu, b0, 2);
            float ra = rsqrt_fast(fmaf(a0, 1.0f / 96.0f, 1e-5f)), rb = rsqrt_fast(fmaf(b0, 1.0f / 96.0f, 1e-5f));
#pragma unroll
            for (int j = 0; j < 3; j++) {
                const float* a = &acc[16 * j];
                uint4 va = make_uint4(pack_bf16(a[0] * ra, a[1] * ra), pack_bf16(a[4] * ra, a[5] * ra),
                                      pack_bf16(a[8] * ra, a[9] * ra), pack_bf16(a[12] * ra, a[13] * ra));
                uint4 vb = make_uint4(pack_bf16(a[2] * rb, a[3] * rb), pack_bf16(a[6] * rb, a[7] * rb),
                                      pack_bf16(a[10] * rb, a[11] * rb), pack_bf16(a[14] * rb, a[15] * rb));
                *reinterpret_cast<uint4*>(ob + curA + 64 * j) = va;
                *reinterpret_cast<uint4*>(ob + curB + 64 * j) = vb;
            }
        }
    }
}

}

extern "C" void kernel_launch(void* const* d_in, const int* in_sizes, int n_in, void* d_out, int out_size) {
    (void)in_sizes; (void)n_in; (void)out_size;
    static int sms = 0;
    if (sms == 0) {
        int dev = 0;
        cudaGetDevice(&dev);
        cudaDeviceGetAttribute(&sms, cudaDevAttrMultiProcessorCount, dev);
        cudaFuncSetAttribute(swin_attn_kernel, cudaFuncAttributeMaxDynamicSharedMemorySize, SMEM_BYTES);
    }
    swin_attn_kernel<<<sms, NTHREADS, SMEM_BYTES>>>(
        (const __nv_bfloat16*)d_in[0], (const __nv_bfloat16*)d_in[1], (const __nv_bfloat16*)d_in[2],
        (const __nv_bfloat16*)d_in[3], (const __nv_bfloat16*)d_in[4], (const __nv_bfloat16*)d_in[5],
        (const __nv_bfloat16*)d_in[6], (const int*)d_in[7], (const __nv_bfloat16*)d_in[8], (__nv_bfloat16*)d_out);
}
```

```cpp
#include <cuda.h>
#include <cuda_runtime.h>
#include <cuda_bf16.h>
#include <cuda_fp16.h>
#include <stdint.h>

#define TL_CLK(i)
#define TL_GT(i)
#define TL_DUMP
#define TL_EXTRA 0
#define TL(k)

#define REL_TOK if (elect_one()) asm volatile("mbarrier.arrive.shared::cta.b64 _, [%0];" ::"r"(sbase + OFF_TOK + 8 * ((wi + 4) & 15)) : "memory")
#define REL 0
#define ACQ 1
#define ACQ_TOK mbar_wait(n > 0 ? sbase + OFF_TOK + 8 * wi : mbar_c, n > 0 ? ((n - 1) >> 2) & 1 : 0)
#define ROT 5
#define QSPLIT 2
#define EXP_REL 4
namespace {

constexpr int NWG      = 4;
constexpr int NTHREADS = NWG * 128;
constexpr int IMG      = 384;
constexpr int WSIDE    = 48;
constexpr int NWIN     = WSIDE * WSIDE;
constexpr int NTAB     = 225;
constexpr float LOG2E  = 1.4426950408889634f;
constexpr float SS_MIN = 1.0f / 512.0f, SS_MAX = 60000.0f;

constexpr int OFF_ZLO  = 0;
constexpr int OFF_WQKV = 1024;
constexpr int WQKV_LBO = 36 * 128;
constexpr int OFF_WO   = OFF_WQKV + 12 * WQKV_LBO;
constexpr int WO_LBO   = 12 * 128;
constexpr int OFF_BIAS = OFF_WO + 12 * WO_LBO;
constexpr int V_HEAD   = 4 * 1024;
constexpr int K_HEAD   = 3 * 1024 + 32;
constexpr int V_STRIDE = 4 * V_HEAD;
constexpr int XTILE    = 3072;
constexpr int K_STRIDE = 13 * 1024;
constexpr int OFF_K    = OFF_BIAS + 32768;
constexpr int OFF_V    = OFF_K + NWG * K_STRIDE;
constexpr int OFF_ZHI  = OFF_V + NWG * V_STRIDE;
constexpr int OFF_TAB  = OFF_ZHI + 1024;
constexpr int OFF_MBAR = OFF_TAB + 2400;
constexpr int OFF_TOK  = OFF_MBAR + 176;
constexpr int OFF_QS   = OFF_TOK + 128;
constexpr int SMEM_BYTES = OFF_QS + 16;
constexpr int OFF_PAR  = OFF_V + 55296;
static_assert(OFF_K % 1024 == 0 && OFF_V % 128 == 0 && V_STRIDE % 128 == 0 && OFF_WO % 128 == 0 && OFF_BIAS % 128 == 0, "alignment");
static_assert(4 * K_HEAD <= K_STRIDE && 55296 + 1280 <= NWG * V_STRIDE && OFF_MBAR % 8 == 0, "layout");
static_assert(SMEM_BYTES + TL_EXTRA <= 232448, "smem");

__device__ __forceinline__ uint64_t make_desc(uint32_t addr, uint32_t lbo, uint32_t sbo) {
    return (uint64_t)((addr >> 4) | ((lbo >> 4) << 16)) | ((uint64_t)(sbo >> 4) << 32);
}

__device__ __forceinline__ void wg_fence()  { asm volatile("wgmma.fence.sync.aligned;" ::: "memory"); }
__device__ __forceinline__ void wg_commit() { asm volatile("wgmma.commit_group.sync.aligned;" ::: "memory"); }
template <int N> __device__ __forceinline__ void wg_wait() {
    asm volatile("wgmma.wait_group.sync.aligned %0;" ::"n"(N) : "memory");
}
template <int N> __device__ __forceinline__ void pin(float (&d)[N]) {
#pragma unroll
    for (int i = 0; i < N; i++) asm volatile("" : "+f"(d[i])::"memory");
}
template <int N> __device__ __forceinline__ void pin(uint32_t (&d)[N]) {
#pragma unroll
    for (int i = 0; i < N; i++) asm volatile("" : "+r"(d[i])::"memory");
}

#define F8(C, d, o) C(d[o + 0]), C(d[o + 1]), C(d[o + 2]), C(d[o + 3]), C(d[o + 4]), C(d[o + 5]), C(d[o + 6]), C(d[o + 7])
#define RW_F(x) "+f"(x)
#define WO_F(x) "=f"(x)
#define RW_R(x) "+r"(x)
#define WO_R(x) "=r"(x)

#define N96_REGS                                                                                  \
    "{%0,%1,%2,%3,%4,%5,%6,%7,%8,%9,%10,%11,%12,%13,%14,%15,%16,%17,%18,%19,%20,%21,%22,%23,"     \
    "%24,%25,%26,%27,%28,%29,%30,%31,%32,%33,%34,%35,%36,%37,%38,%39,%40,%41,%42,%43,%44,%45,%46,%47}"

#define MMA_N96(TY, SD, C)                                                                                           \
    asm volatile("wgmma.mma_async.sync.aligned.m64n96k16.f32." TY "." TY " " N96_REGS                                \
                 ", {%48,%49,%50,%51}, %52, " SD ", 1, 1, 1;"                                                        \
                 : F8(C, d, 0), F8(C, d, 8), F8(C, d, 16), F8(C, d, 24), F8(C, d, 32), F8(C, d, 40)                  \
                 : "r"(a[0]), "r"(a[1]), "r"(a[2]), "r"(a[3]), "l"(db))
template <bool FIRST, bool BF>
__device__ __forceinline__ void mma_n96(float (&d)[48], const uint32_t* a, uint64_t db) {
    if (FIRST) { if (BF) MMA_N96("bf16", "0", WO_F); else MMA_N96("f16", "0", WO_F); }
    else       { if (BF) MMA_N96("bf16", "1", RW_F); else MMA_N96("f16", "1", RW_F); }
}
template <bool BF>
__device__ __forceinline__ void gemm96(float (&d)[48], const uint32_t (&a)[24], uint64_t db, uint32_t kstep) {
    wg_fence();
    mma_n96<true, BF>(d, &a[0], db);
#pragma unroll
    for (int s = 1; s < 6; s++) mma_n96<false, BF>(d, &a[4 * s], db + (uint64_t)(s * (kstep >> 4)));
    wg_commit();
}
#define N24_REGS "{%0,%1,%2,%3,%4,%5,%6,%7,%8,%9,%10,%11,%12,%13,%14,%15,%16,%17,%18,%19,%20,%21,%22,%23}"
#define MMA_H192(SD, C)                                                                                              \
    asm volatile("wgmma.mma_async.sync.aligned.m64n192k16.f16.f16.f16 " N96_REGS ", {%48,%49,%50,%51}, %52, " SD ", 1, 1, 1;" \
                 : F8(C, d, 0), F8(C, d, 8), F8(C, d, 16), F8(C, d, 24), F8(C, d, 32), F8(C, d, 40)                  \
                 : "r"(a[4 * s]), "r"(a[4 * s + 1]), "r"(a[4 * s + 2]), "r"(a[4 * s + 3]), "l"(db + (uint64_t)(s * (kstep >> 4))))
#define MMA_H96(SD, C)                                                                                               \
    asm volatile("wgmma.mma_async.sync.aligned.m64n96k16.f16.f16.f16 " N24_REGS ", {%24,%25,%26,%27}, %28, " SD ", 1, 1, 1;" \
                 : F8(C, d, 0), F8(C, d, 8), F8(C, d, 16)                                                            \
                 : "r"(a[4 * s]), "r"(a[4 * s + 1]), "r"(a[4 * s + 2]), "r"(a[4 * s + 3]), "l"(db + (uint64_t)(s * (kstep >> 4))))
__device__ __forceinline__ void proj96(uint32_t (&d)[24], const uint32_t (&a)[24], uint64_t db, uint32_t kstep) {
#pragma unroll
    for (int s = 0; s < 6; s++) { if (s == 0) MMA_H96("0", WO_R); else MMA_H96("1", RW_R); }
    wg_commit();
}
#define N16_REGS "{%0,%1,%2,%3,%4,%5,%6,%7,%8,%9,%10,%11,%12,%13,%14,%15}"
__device__ __forceinline__ void mma_qk(uint32_t (&d)[16], const uint32_t* a, uint64_t db) {
    asm volatile("wgmma.mma_async.sync.aligned.m64n64k16.f16.f16.f16 " N16_REGS
                 ", {%16,%17,%18,%19}, %20, 1, 1, 1, 0;"
                 : F8(RW_R, d, 0), F8(RW_R, d, 8)
                 : "r"(a[0]), "r"(a[1]), "r"(a[2]), "r"(a[3]), "l"(db));
}
template <bool FIRST>
__device__ __forceinline__ void mma_pv(uint32_t (&d)[8], const uint32_t* a, uint64_t db) {
    if (FIRST) {
        asm volatile("wgmma.mma_async.sync.aligned.m64n32k16.f16.f16.f16 {%0,%1,%2,%3,%4,%5,%6,%7}, {%8,%9,%10,%11}, %12, 0, 1, 1, 1;"
                     : F8(WO_R, d, 0) : "r"(a[0]), "r"(a[1]), "r"(a[2]), "r"(a[3]), "l"(db));
    } else {
        asm volatile("wgmma.mma_async.sync.aligned.m64n32k16.f16.f16.f16 {%0,%1,%2,%3,%4,%5,%6,%7}, {%8,%9,%10,%11}, %12, 1, 1, 1, 1;"
                     : F8(RW_R, d, 0) : "r"(a[0]), "r"(a[1]), "r"(a[2]), "r"(a[3]), "l"(db));
    }
}

__device__ __forceinline__ uint32_t pack_f16(float lo, float hi) {
    uint32_t r; asm("cvt.rn.f16x2.f32 %0, %1, %2;" : "=r"(r) : "f"(hi), "f"(lo)); return r;
}
__device__ __forceinline__ uint32_t pack_f16_sat(float lo, float hi) {
    uint32_t r; asm("cvt.rn.satfinite.f16x2.f32 %0, %1, %2;" : "=r"(r) : "f"(hi), "f"(lo)); return r;
}
__device__ __forceinline__ uint32_t pack_bf16(float lo, float hi) {
    uint32_t r; asm("cvt.rn.bf16x2.f32 %0, %1, %2;" : "=r"(r) : "f"(hi), "f"(lo)); return r;
}
__device__ __forceinline__ float bf_lo(uint32_t v) { return __uint_as_float(v << 16); }
__device__ __forceinline__ float bf_hi(uint32_t v) { return __uint_as_float(v & 0xFFFF0000u); }
__device__ __forceinline__ float bf_round(float x) { return bf_lo(pack_bf16(x, 0.f)); }
__device__ __forceinline__ __half2 as_h2(uint32_t v) { return *reinterpret_cast<__half2*>(&v); }
__device__ __forceinline__ uint32_t as_u32(__half2 v) { return *reinterpret_cast<uint32_t*>(&v); }
__device__ __forceinline__ uint32_t ex2_h2(uint32_t v) {
    uint32_t r; asm("ex2.approx.f16x2 %0, %1;" : "=r"(r) : "r"(v)); return r;
}
__device__ __forceinline__ uint32_t bf2h(uint32_t v) { return pack_f16_sat(bf_lo(v), bf_hi(v)); }
#define HM(x, r) as_u32(__hmul2(as_h2(x), r))
__device__ __forceinline__ float rsqrt_fast(float x) {
    float r; asm("rsqrt.approx.ftz.f32 %0, %1;" : "=f"(r) : "f"(x)); return r;
}
__device__ __forceinline__ float ex2_fast(float x) {
    float r; asm("ex2.approx.ftz.f32 %0, %1;" : "=f"(r) : "f"(x)); return r;
}
__device__ __forceinline__ float rcp_fast(float x) {
    float r; asm("rcp.approx.ftz.f32 %0, %1;" : "=f"(r) : "f"(x)); return r;
}
__device__ __forceinline__ void ldg_stream(uint32_t* r, const void* p) {
    asm volatile("ld.global.L1::no_allocate.v4.u32 {%0,%1,%2,%3}, [%4];"
                 : "=r"(r[0]), "=r"(r[1]), "=r"(r[2]), "=r"(r[3]) : "l"(p) : "memory");
}
__device__ __forceinline__ uint32_t ldg_const32(const void* p) {
    uint32_t r; asm volatile("ld.global.nc.u32 %0, [%1];" : "=r"(r) : "l"(p)); return r;
}
__device__ __forceinline__ void sts128(uint32_t addr, uint32_t a, uint32_t b, uint32_t c, uint32_t d) {
    asm volatile("st.shared.v4.u32 [%0], {%1,%2,%3,%4};" ::"r"(addr), "r"(a), "r"(b), "r"(c), "r"(d) : "memory");
}
__device__ __forceinline__ void lds128(uint32_t* r, uint32_t addr) {
    asm volatile("ld.shared.v4.u32 {%0,%1,%2,%3}, [%4];" : "=r"(r[0]), "=r"(r[1]), "=r"(r[2]), "=r"(r[3]) : "r"(addr));
}
__device__ __forceinline__ void bar_sync(int id, int n)   { asm volatile("bar.sync %0, %1;" ::"r"(id), "r"(n) : "memory"); }
__device__ __forceinline__ void fence_async() { asm volatile("fence.proxy.async.shared::cta;" ::: "memory"); }
template <int K>
__device__ __forceinline__ bool again(int nonneg) {
    uint32_t r;
    asm volatile("{ .reg .pred p; setp.eq.s32 p, %1, %2; selp.u32 %0, 1, 0, p; }" : "=r"(r) : "r"(nonneg), "n"(-1 - K) : "memory");
    return r != 0;
}
#define STAGE_BEGIN _Pragma("unroll 1") do {
#define STAGE_END(k) } while (again<k>(n));
__device__ __forceinline__ void stsm4(uint32_t addr, const uint32_t* r) {
    asm volatile("stmatrix.sync.aligned.m8n8.x4.shared.b16 [%0], {%1,%2,%3,%4};"
                 ::"r"(addr), "r"(r[0]), "r"(r[1]), "r"(r[2]), "r"(r[3]) : "memory");
}
__device__ __forceinline__ void ldsm4(uint32_t* r, uint32_t addr) {
    asm volatile("ldmatrix.sync.aligned.m8n8.x4.shared.b16 {%0,%1,%2,%3}, [%4];"
                 : "=r"(r[0]), "=r"(r[1]), "=r"(r[2]), "=r"(r[3]) : "r"(addr) : "memory");
}
__device__ __forceinline__ void mbar_init(uint32_t mbar, uint32_t count) {
    asm volatile("mbarrier.init.shared::cta.b64 [%0], %1;" ::"r"(mbar), "r"(count) : "memory");
}
__device__ __forceinline__ void mbar_expect(uint32_t mbar, uint32_t bytes) {
    asm volatile("mbarrier.arrive.expect_tx.shared::cta.b64 _, [%0], %1;" ::"r"(mbar), "r"(bytes) : "memory");
}
__device__ __forceinline__ void mbar_wait(uint32_t mbar, uint32_t parity) {
    uint32_t ok;
    int spins = 0;
    do {
        asm volatile("{ .reg .pred p; mbarrier.try_wait.parity.shared::cta.b64 p, [%1], %2; selp.u32 %0, 1, 0, p; }"
                     : "=r"(ok) : "r"(mbar), "r"(parity) : "memory");
    } while (!ok && ++spins < (1 << 22));
}
__device__ __forceinline__ bool elect_one() {
    uint32_t p;
    asm volatile("{ .reg .pred p; elect.sync _|p, 0xffffffff; selp.u32 %0, 1, 0, p; }" : "=r"(p));
    return p != 0;
}
__device__ __forceinline__ void bulk_copy(uint32_t dst, const void* src, uint32_t bytes, uint32_t mbar) {
    asm volatile("cp.async.bulk.shared::cluster.global.mbarrier::complete_tx::bytes [%0], [%1], %2, [%3];"
                 ::"r"(dst), "l"(src), "r"(bytes), "r"(mbar) : "memory");
}
__device__ __forceinline__ void quadrant_xy(int win, int w, int& x4, int& y) {
    int wy = win / WSIDE, wx = win - wy * WSIDE;
    y  = wy * 8 + 4 + 4 * (w >> 1);
    x4 = wx * 2 + 1 + (w & 1);
    if (y >= IMG) y -= IMG;
    if (x4 >= IMG / 4) x4 -= IMG / 4;
}
__device__ __forceinline__ void issue_x(const CUtensorMap* tm, int win, int w, uint32_t dst, uint32_t mbar) {
    int x4, y;
    quadrant_xy(win, w, x4, y);
    mbar_expect(mbar, XTILE);
    asm volatile("cp.async.bulk.tensor.3d.shared::cluster.global.mbarrier::complete_tx::bytes [%0], [%1, {%2, %3, %4}], [%5];"
                 ::"r"(dst), "l"(tm), "r"(0), "r"(6 * x4), "r"(y), "r"(mbar) : "memory");
}
__device__ __forceinline__ int wrap(int p, int n) { return p >= n ? p - n : p; }
__device__ __forceinline__ uint32_t swz(uint32_t lin) { return lin ^ ((lin >> 3) & 0x70); }
__device__ __forceinline__ uint32_t lin_x(uint32_t l16) { return (l16 & 112) * 24 + ((l16 >> 7) & 1) * 192 + ((l16 >> 4) & 16); }
__device__ __forceinline__ uint32_t tab_slot(uint32_t idx) { return (idx + 5 * ((idx * 4370u) >> 16)) * 8; }

__device__ __forceinline__ int window_id(int n, int nblk, int pos) { return NWIN - 1 - (n * nblk + pos); }

struct Params {
    const __nv_bfloat16 *wqkv, *cpb_w1, *cpb_w2, *rel_coords, *wo, *logit_scale, *mask;
    const int* rel_idx;
    __nv_bfloat16* out;
    int nblk, nfull, last_rot, rem, rot;
};

__global__ void __launch_bounds__(NTHREADS, 1)
swin_attn_kernel(const Params prm, const __grid_constant__ CUtensorMap tmx) {
    extern __shared__ __align__(1024) uint8_t smem[];
    const uint32_t sbase = (uint32_t)__cvta_generic_to_shared(smem);
    const int tid  = threadIdx.x;
    TL_CLK(2);
    const int wi = __shfl_sync(0xffffffffu, tid >> 5, 0);
    const uint32_t mbar_w = sbase + OFF_MBAR + 128, mbar_b = mbar_w + 8, mbar_p = mbar_w + 16, mbar_o = mbar_w + 24, mbar_r = mbar_w + 32, mbar_c = mbar_w + 40;
    if (wi == 0 && elect_one()) {
        mbar_init(mbar_w, 1);
        mbar_init(mbar_p, 1);
        fence_async();
        mbar_expect(mbar_p, 64 + 128 + 896);
        mbar_expect(mbar_w, 55296);
        bulk_copy(sbase + OFF_PAR, prm.cpb_w1, 64, mbar_p);
        bulk_copy(sbase + OFF_PAR + 128, prm.cpb_w2, 128, mbar_p);
        bulk_copy(sbase + OFF_PAR + 256, prm.rel_coords, 896, mbar_p);
        bulk_copy(sbase + OFF_V, prm.wqkv, 55296, mbar_w);
    }
    const int lane = tid & 31;
    const int g = lane >> 2, c = lane & 3;
    const int wg = wi >> 2, w = wi & 3;
    const uint32_t mbar = sbase + OFF_MBAR + 8 * wi;
    if (elect_one()) {
        mbar_init(mbar, 1);
        mbar_init(sbase + OFF_TOK + 8 * wi, 1);
        if (wi == 1) asm volatile("prefetch.tensormap [%0];" ::"l"(&tmx) : "memory");
        if (wi == 4) {
            mbar_init(mbar_o, 1);
            mbar_init(mbar_b, 256);
            mbar_init(mbar_c, 256);
            mbar_init(mbar_r, NTHREADS);
        }
        fence_async();
    }
    const int nblk = prm.nblk;
    const int cnt = prm.nfull + (wrap(blockIdx.x + prm.last_rot, nblk) < prm.rem ? 1 : 0);
    int n = wg;
    int pos = wrap(blockIdx.x + prm.rot * wg, nblk);
    const char* maskb = reinterpret_cast<const char*>(prm.mask) + (32 * (w >> 1) + 4 * (w & 1)) * 128;
    const uint32_t vreg = sbase + OFF_V + wg * V_STRIDE;
    const uint32_t kreg = sbase + OFF_K + wg * K_STRIDE;
    const uint32_t lane16 = lane * 16;
    int win = max(window_id(n, nblk, pos), 0);
    TL_CLK(3);
    __syncthreads();
    TL_CLK(4);
    uint32_t mr[16];
    const int ent = tid - 256;
    if (wg < 2) {
        if (wi == 4 && elect_one()) {
            mbar_expect(mbar_o, 16384 + 18432);
            bulk_copy(sbase + OFF_BIAS, prm.rel_idx, 16384, mbar_o);
            bulk_copy(sbase + OFF_WO, prm.wo, 18432, mbar_o);
        }
        if (wg == 1) mbar_wait(mbar_w, 0);
        if (elect_one()) issue_x(&tmx, win, w, kreg + w * XTILE, mbar);
        __syncwarp();
#pragma unroll
        for (int i = 0; i < 4; i++) ldg_stream(&mr[4 * i], maskb + (size_t)win * 8192 + lane16 + 1024 * i);
        if (wg == 0) sts128(sbase + (w < 2 ? OFF_ZLO : OFF_ZHI - 1024) + tid * 16, 0u, 0u, 0u, 0u);
    } else {
        uint32_t small = 0;
        if (wi == 15) small = ldg_const32(lane < 16 ? reinterpret_cast<const uint32_t*>(prm.rel_coords) + NTAB - 1
                                                    : reinterpret_cast<const uint32_t*>(prm.logit_scale) + (c >> 1));
        mbar_wait(mbar_p, 0);
        TL_CLK(5);
            uint32_t w1[16], w2[32];
#pragma unroll
            for (int i = 0; i < 4; i++) lds128(&w1[4 * i], sbase + OFF_PAR + 16 * i);
#pragma unroll
            for (int i = 0; i < 8; i++) lds128(&w2[4 * i], sbase + OFF_PAR + 128 + 16 * i);
            const uint32_t rc = ent >= NTAB - 1 ? small : *reinterpret_cast<const uint32_t*>(smem + OFF_PAR + 256 + 4 * ent);
            float r0 = bf_lo(rc), r1 = bf_hi(rc), z[4] = {0.f, 0.f, 0.f, 0.f};
#pragma unroll
            for (int j = 0; j < 16; j += 2) {
                uint32_t hp = pack_bf16(fmaf(r1, bf_lo(w1[8 + (j >> 1)]), r0 * bf_lo(w1[j >> 1])),
                                        fmaf(r1, bf_hi(w1[8 + (j >> 1)]), r0 * bf_hi(w1[j >> 1])));
                float h0 = bf_lo(hp), h1 = bf_hi(hp);
                h0 = h0 > 0.f ? h0 : h0 * 0.f;
                h1 = h1 > 0.f ? h1 : h1 * 0.f;
                z[0] = fmaf(h0, bf_lo(w2[2 * j]), z[0]);     z[1] = fmaf(h0, bf_hi(w2[2 * j]), z[1]);
                z[2] = fmaf(h0, bf_lo(w2[2 * j + 1]), z[2]); z[3] = fmaf(h0, bf_hi(w2[2 * j + 1]), z[3]);
                z[0] = fmaf(h1, bf_lo(w2[2 * j + 2]), z[0]); z[1] = fmaf(h1, bf_hi(w2[2 * j + 2]), z[1]);
                z[2] = fmaf(h1, bf_lo(w2[2 * j + 3]), z[2]); z[3] = fmaf(h1, bf_hi(w2[2 * j + 3]), z[3]);
            }
#pragma unroll
            for (int h = 0; h < 4; h++) z[h] = bf_round(rcp_fast(1.0f + ex2_fast(-LOG2E * bf_round(z[h])))) * (16.0f * LOG2E);
            if (ent < NTAB)
                asm volatile("st.shared.v2.u32 [%0], {%1,%2};" ::"r"(sbase + OFF_TAB + tab_slot(ent)), "r"(pack_f16(z[0], z[1])),
                             "r"(pack_f16(z[2], z[3])) : "memory");
        if (tid >= NTHREADS - 4) {
            float ls = bf_round(fminf(fmaxf((c & 1) ? bf_hi(small) : bf_lo(small), -100.0f), 4.6052f));
            float qs = bf_round(ex2_fast(ls * LOG2E)) * LOG2E;
            asm volatile("st.shared.f32 [%0], %1;" ::"r"(sbase + OFF_QS + c * 4), "f"(qs) : "memory");
        }
        TL_CLK(6);
    }
    {
        const int k8 = tid & 7, rot = k8 >> 1;
        uint32_t src[2], dst[2];
        {
            int rest = tid >> 3;
            int pj = rest / 12, kg = rest - 12 * pj;
            src[0] = sbase + OFF_V + (kg * 8 + k8) * 576 + (pj < 3 ? 384 + 64 * pj : 64 * pj - 192);
            dst[0] = sbase + OFF_WQKV + kg * WQKV_LBO + (12 + 4 * pj) * 128 + k8 * 16;
            if (wi < 9) {
                int j = pj + (rot == 3 ? 0 : rot);
                j -= j >= 3 ? 3 : 0;
                src[1] = sbase + OFF_V + (kg * 8 + k8) * 576 + 192 + 16 * j;
                dst[1] = sbase + OFF_WQKV + kg * WQKV_LBO + 4 * j * 128 + k8 * 16;
            } else {
                kg = rest - 32;
                src[1] = sbase + OFF_V + (kg * 8 + k8) * 576 + 128;
                dst[1] = sbase + OFF_WQKV + kg * WQKV_LBO + 32 * 128 + k8 * 16;
            }
        }
        TL_CLK(7);
        mbar_wait(mbar_w, 0);
        TL_CLK(8);
        uint32_t v[2][4][4];
#pragma unroll
        for (int q = 0; q < 4; q++) lds128(v[0][q], src[0] + 16 * ((q + rot) & 3));
        if (wi < 11) {
#pragma unroll
            for (int q = 0; q < 4; q++) lds128(v[1][q], src[1] + (wi < 9 ? 48 * q : 16 * ((q + rot) & 3)));
        }
#pragma unroll
        for (int q = 0; q < 4; q++)
            sts128(dst[0] + 128 * ((q + rot) & 3), bf2h(v[0][q][0]), bf2h(v[0][q][1]), bf2h(v[0][q][2]), bf2h(v[0][q][3]));
        if (wi < 9) {
#pragma unroll
            for (int q = 0; q < 4; q++) sts128(dst[1] + 128 * q, bf2h(v[1][0][q]), bf2h(v[1][1][q]), bf2h(v[1][2][q]), bf2h(v[1][3][q]));
        } else if (wi < 11) {
#pragma unroll
            for (int q = 0; q < 4; q++)
                sts128(dst[1] + 128 * ((q + rot) & 3), bf2h(v[1][q][0]), bf2h(v[1][q][1]), bf2h(v[1][q][2]), bf2h(v[1][q][3]));
        }
        fence_async();
        asm volatile("mbarrier.arrive.shared::cta.b64 _, [%0];" ::"r"(mbar_r) : "memory");
        TL_CLK(9);
    }
    if (wg >= 2) {
        uint32_t wov[2][12];
        int4 ri[2][2];
        mbar_wait(mbar_o, 0);
#pragma unroll
        for (int r = 0; r < 2; r++)
#pragma unroll
            for (int j = 0; j < 3; j++) lds128(&wov[r][4 * j], sbase + OFF_WO + min(64 * r + (ent >> 2), 95) * 192 + 64 * j + 16 * c);
#pragma unroll
        for (int i = 0; i < 2; i++) {
            const int bw = wg - 2 + 2 * i;
            const uint32_t p = sbase + OFF_BIAS + ((32 * (bw >> 1) + 4 * (bw & 1) + 8 * (g >> 1) + 2 * (g & 1)) * 64 + 32 * (w >> 1) + 8 * c + 4 * (w & 1)) * 4;
            lds128(reinterpret_cast<uint32_t*>(&ri[i][0]), p);
            lds128(reinterpret_cast<uint32_t*>(&ri[i][1]), p + 256);
        }
        bar_sync(9, 256);
#pragma unroll
        for (int i = 0; i < 2; i++) {
            const int4 ra = ri[i][0], rb = ri[i][1];
            int id[8] = {ra.x, ra.z, rb.x, rb.z, ra.y, ra.w, rb.y, rb.w};
            uint2 e[8];
#pragma unroll
            for (int k = 0; k < 8; k++)
                e[k] = *reinterpret_cast<const uint2*>(smem + OFF_TAB + tab_slot(min((unsigned)id[k], (unsigned)(NTAB - 1))));
            uint32_t dst = sbase + OFF_BIAS + (ent + 256 * i) * 16;
            sts128(dst,         __byte_perm(e[0].x, e[1].x, 0x5410), __byte_perm(e[2].x, e[3].x, 0x5410),
                                __byte_perm(e[4].x, e[5].x, 0x5410), __byte_perm(e[6].x, e[7].x, 0x5410));
            sts128(dst + 8192,  __byte_perm(e[0].x, e[1].x, 0x7632), __byte_perm(e[2].x, e[3].x, 0x7632),
                                __byte_perm(e[4].x, e[5].x, 0x7632), __byte_perm(e[6].x, e[7].x, 0x7632));
            sts128(dst + 16384, __byte_perm(e[0].y, e[1].y, 0x5410), __byte_perm(e[2].y, e[3].y, 0x5410),
                                __byte_perm(e[4].y, e[5].y, 0x5410), __byte_perm(e[6].y, e[7].y, 0x5410));
            sts128(dst + 24576, __byte_perm(e[0].y, e[1].y, 0x7632), __byte_perm(e[2].y, e[3].y, 0x7632),
                                __byte_perm(e[4].y, e[5].y, 0x7632), __byte_perm(e[6].y, e[7].y, 0x7632));
        }
        asm volatile("mbarrier.arrive.shared::cta.b64 _, [%0];" ::"r"(mbar_b) : "memory");
        if (n < cnt && elect_one()) issue_x(&tmx, win, w, kreg + w * XTILE, mbar);
        __syncwarp();
#pragma unroll
        for (int i = 0; i < 4; i++) ldg_stream(&mr[4 * i], maskb + (size_t)win * 8192 + lane16 + 1024 * i);
#pragma unroll
        for (int r = 0; r < 2; r++) {
            const int krow = 64 * r + (ent >> 2);
            float s = 0.f;
#pragma unroll
            for (int i = 0; i < 12; i++) s += bf_lo(wov[r][i]) + bf_hi(wov[r][i]);
            s += __shfl_xor_sync(0xffffffffu, s, 1);
            s += __shfl_xor_sync(0xffffffffu, s, 2);
            const float mean = s * (1.0f / 96.0f);
            const uint32_t dst = sbase + OFF_WO + (krow >> 3) * WO_LBO + (krow & 7) * 16 + 4 * c;
            if (krow < 96) {
#pragma unroll
                for (int i = 0; i < 12; i++) {
                    uint32_t p = pack_f16_sat(bf_lo(wov[r][i]) - mean, bf_hi(wov[r][i]) - mean);
                    asm volatile("st.shared.u32 [%0], %1;" ::"r"(dst + i * 128), "r"(p) : "memory");
                }
            }
        }
        fence_async();
        asm volatile("mbarrier.arrive.shared::cta.b64 _, [%0];" ::"r"(mbar_c) : "memory");
    }

    const uint32_t st_k = kreg + c * K_HEAD + (16 * w + g) * 16;
    const uint32_t xt = kreg + w * XTILE;
    const uint32_t ubias = sbase + OFF_BIAS + w * 2048;
    const uint64_t dw0  = make_desc(sbase + OFF_WQKV, WQKV_LBO, 128);
    const uint64_t dwo0 = make_desc(sbase + OFF_WO, WO_LBO, 128);
    const uint64_t dk0  = make_desc(kreg, 1024, 128);
    const uint64_t dkh0 = make_desc(kreg + 2048, sbase + OFF_ZHI - (kreg + 2048), 128);
    const uint64_t dkl0 = make_desc(sbase + OFF_ZLO, kreg + K_HEAD - (sbase + OFF_ZLO), 128);
    const uint64_t dv0  = make_desc(vreg, 128, 1024);
    TL_CLK(11);

    if (n >= cnt) return;
    uint32_t xr[24], ak[24];
    mbar_wait(mbar, 0);
#pragma unroll
    for (int s = 0; s < 6; s++) ldsm4(&xr[4 * s], xt + (swz(lin_x(lane16) + 64 * (s >> 1)) ^ (32 * (s & 1))));
#pragma unroll
    for (int i = 0; i < 24; i++) xr[i] = bf2h(xr[i]);
    mbar_wait(mbar_r, 0);
    TL_CLK(10);
    const float tau = *reinterpret_cast<const float*>(smem + OFF_QS + c * 4);
    wg_fence();
    proj96(ak, xr, dw0, 2 * WQKV_LBO);
#pragma unroll
    for (int i = 0; i < 2; i++) {
        int idx = (tid & 127) + 128 * i;
        sts128(vreg + (idx >> 6) * V_HEAD + 3 * 1024 + (idx & 63) * 16, 0x3C003C00u, 0x3C003C00u, 0x3C003C00u, 0x3C003C00u);
    }
    bar_sync(1 + wg, 128);
    wg_wait<0>();
    pin(ak);
    bool has_mask;
    {
        uint32_t any = ak[23] & 0x80008000u;
#pragma unroll
        for (int i = 0; i < 8; i++) asm volatile("lop3.b32 %0, %0, %1, %2, 0xFE;" : "+r"(any) : "r"(mr[2 * i]), "r"(mr[2 * i + 1]));
        has_mask = __any_sync(0xffffffffu, (any & 0x7FFF7FFFu) != 0);
    }

    for (;; n += NWG) {
        TL(0);
        pos = wrap(pos + NWG * prm.rot, nblk);
        const int nwin = window_id(n + NWG, nblk, pos);
        const bool more = n + NWG < cnt;
        const uint32_t z32 = n >> 30;
        const uint64_t zero = z32;
        const uint64_t dw = dw0 + zero;
        uint32_t av[24], qf[24];
        TL(2);
        wg_fence();
        proj96(av, xr, dw + ((12 * 128) >> 4), 2 * WQKV_LBO);
        {
            __half2 sa = __hmul2(as_h2(ak[0]), as_h2(ak[0])), sb = __hmul2(as_h2(ak[1]), as_h2(ak[1]));
            __half2 ta = __hmul2(as_h2(ak[2]), as_h2(ak[2])), tb = __hmul2(as_h2(ak[3]), as_h2(ak[3]));
#pragma unroll
            for (int t = 2; t < 12; t += 2) {
                sa = __hfma2(as_h2(ak[2 * t]), as_h2(ak[2 * t]), sa);         sb = __hfma2(as_h2(ak[2 * t + 1]), as_h2(ak[2 * t + 1]), sb);
                ta = __hfma2(as_h2(ak[2 * t + 2]), as_h2(ak[2 * t + 2]), ta); tb = __hfma2(as_h2(ak[2 * t + 3]), as_h2(ak[2 * t + 3]), tb);
            }
            sa = __hadd2(sa, ta); sb = __hadd2(sb, tb);
            float fa = __low2float(sa) + __high2float(sa), fb = __low2float(sb) + __high2float(sb);
            __half2 r = as_h2(pack_f16_sat(rsqrt_fast(fa) * tau, rsqrt_fast(fb) * tau));
            if (__any_sync(0xffffffffu, !(fminf(fa, fb) >= SS_MIN && fa + fb < SS_MAX))) {
                fa = 1e-12f; fb = 1e-12f;
#pragma unroll
                for (int t = 0; t < 12; t++) {
                    float2 u = __half22float2(as_h2(ak[2 * t])), v = __half22float2(as_h2(ak[2 * t + 1]));
                    fa = fmaf(u.x, u.x, fmaf(u.y, u.y, fa)); fb = fmaf(v.x, v.x, fmaf(v.y, v.y, fb));
                }
                fa = rsqrt_fast(fa) * tau; fb = rsqrt_fast(fb) * tau;
#pragma unroll
                for (int t = 0; t < 12; t++) {
                    float2 u = __half22float2(as_h2(ak[2 * t])), v = __half22float2(as_h2(ak[2 * t + 1]));
                    ak[2 * t] = pack_f16(u.x * fa, u.y * fa); ak[2 * t + 1] = pack_f16(v.x * fb, v.y * fb);
                }
                r = as_h2(0x3C003C00u);
            }
            __half2 ra = __low2half2(r), rb = __high2half2(r);
#pragma unroll
            for (int j = 0; j < 3; j++) {
                const uint32_t* a = &ak[8 * j];
                sts128(st_k + j * 1024, HM(a[0], ra), HM(a[2], ra), HM(a[4], ra), HM(a[6], ra));
                sts128(st_k + j * 1024 + 128, HM(a[1], rb), HM(a[3], rb), HM(a[5], rb), HM(a[7], rb));
            }
        }
        TL(3);
        wg_fence();
        proj96(qf, xr, dw + ((24 * 128) >> 4), 2 * WQKV_LBO);
        wg_wait<1>();
        pin(av);
#pragma unroll
        for (int p = 0; p < 6; p++) {
            const int t0 = 2 * p;
            const uint32_t hi = (lane16 + z32) & 256;
            stsm4(lane16 + (t0 % 3 == 2 ? 7 : 3) * hi + (vreg + 256 * w + (t0 / 3) * V_HEAD + (t0 % 3) * 1024), &av[4 * p]);
        }
        TL(4);
        if (has_mask) {
            const uint32_t lv = lane16 + z32;
            asm volatile("prefetch.global.L1 [%0];" ::"l"(maskb + (size_t)win * 8192 + ((lv & 192) * 16 + (lv & 48) * 8)));
        }
        if (n < NWG) mbar_wait(mbar_b, 0);
        uint32_t sacc[4][16];
        wg_wait<0>();
        pin(qf);
        TL(5);
        {
            __half2 ss[4];
            uint32_t sy[4];
#pragma unroll
            for (int h = 0; h < 4; h++) {
                const uint32_t* a = &qf[6 * h];
                __half2 sa = __hmul2(as_h2(a[0]), as_h2(a[0])), sb = __hmul2(as_h2(a[1]), as_h2(a[1]));
                sa = __hfma2(as_h2(a[2]), as_h2(a[2]), sa); sb = __hfma2(as_h2(a[3]), as_h2(a[3]), sb);
                sa = __hfma2(as_h2(a[4]), as_h2(a[4]), sa); sb = __hfma2(as_h2(a[5]), as_h2(a[5]), sb);
                ss[h] = __hadd2(__lows2half2(sa, sb), __highs2half2(sa, sb));
            }
#pragma unroll
            for (int h = 0; h < 4; h++) ss[h] = __hadd2(ss[h], as_h2(__shfl_xor_sync(0xffffffffu, as_u32(ss[h]), 1)));
#pragma unroll
            for (int h = 0; h < 4; h++) sy[h] = __shfl_xor_sync(0xffffffffu, as_u32(ss[h]), 2);
            const uint32_t lb = lane16 + (as_u32(ss[3]) & z32);
#pragma unroll
            for (int h = 0; h < QSPLIT; h++)
#pragma unroll
                for (int q = 0; q < 4; q++) lds128(&sacc[h][4 * q], lb + ubias + h * 8192 + q * 512);
#pragma unroll
            for (int h = 0; h < 4; h++) ss[h] = __hadd2(ss[h], as_h2(sy[h]));
            __half2 rq[4];
#pragma unroll
            for (int h = 0; h < 4; h++) rq[h] = as_h2(pack_f16_sat(rsqrt_fast(__low2float(ss[h])), rsqrt_fast(__high2float(ss[h]))));
            const __half2 smin = __hmin2(__hmin2(ss[0], ss[1]), __hmin2(ss[2], ss[3]));
            const __half2 ssum = __hadd2(__hadd2(ss[0], ss[1]), __hadd2(ss[2], ss[3]));
            if (__any_sync(0xffffffffu, !(__hbge2(smin, __float2half2_rn(SS_MIN)) && __hblt2(ssum, __float2half2_rn(SS_MAX))))) {
#pragma unroll
                for (int h = 0; h < 4; h++) {
                    float fa = 0.25e-12f, fb = 0.25e-12f;
#pragma unroll
                    for (int j = 0; j < 3; j++) {
                        float2 u = __half22float2(as_h2(qf[6 * h + 2 * j])), v = __half22float2(as_h2(qf[6 * h + 2 * j + 1]));
                        fa = fmaf(u.x, u.x, fmaf(u.y, u.y, fa)); fb = fmaf(v.x, v.x, fmaf(v.y, v.y, fb));
                    }
                    fa += __shfl_xor_sync(0xffffffffu, fa, 1); fb += __shfl_xor_sync(0xffffffffu, fb, 1);
                    fa += __shfl_xor_sync(0xffffffffu, fa, 2); fb += __shfl_xor_sync(0xffffffffu, fb, 2);
                    fa = rsqrt_fast(fa); fb = rsqrt_fast(fb);
#pragma unroll
                    for (int j = 0; j < 3; j++) {
                        float2 u = __half22float2(as_h2(qf[6 * h + 2 * j])), v = __half22float2(as_h2(qf[6 * h + 2 * j + 1]));
                        qf[6 * h + 2 * j] = pack_f16(u.x * fa, u.y * fa); qf[6 * h + 2 * j + 1] = pack_f16(v.x * fb, v.y * fb);
                    }
                    rq[h] = as_h2(0x3C003C00u);
                }
            }
#pragma unroll
            for (int h = 0; h < 4; h++) {
                __half2 ra = __low2half2(rq[h]), rb = __high2half2(rq[h]);
#pragma unroll
                for (int j = 0; j < 3; j++) {
                    qf[6 * h + 2 * j]     = HM(qf[6 * h + 2 * j], ra);
                    qf[6 * h + 2 * j + 1] = HM(qf[6 * h + 2 * j + 1], rb);
                }
            }
        }
        fence_async();
        bar_sync(1 + wg, 128);
        TL(6);
        wg_fence();
        {
            const uint64_t dk = dk0 + zero, dkh = dkh0 + zero, dkl = dkl0 + zero;
            constexpr uint64_t HP = (2 * K_HEAD) >> 4;
            mma_qk(sacc[0], &qf[0], dk);
            mma_qk(sacc[0], &qf[4], dkh);
            mma_qk(sacc[1], &qf[4], dkl);
            mma_qk(sacc[1], &qf[8], dk + ((K_HEAD + 1024) >> 4));
            wg_commit();
#pragma unroll
            for (int h = 2; h < 4; h++)
#pragma unroll
                for (int q = 0; q < 4; q++) lds128(&sacc[h][4 * q], lane16 + ubias + h * 8192 + q * 512);
            wg_fence();
            mma_qk(sacc[2], &qf[12], dk + HP);
            mma_qk(sacc[2], &qf[16], dkh + HP - (HP << 16));
            mma_qk(sacc[3], &qf[16], dkl + (HP << 16));
            mma_qk(sacc[3], &qf[20], dk + HP + ((K_HEAD + 1024) >> 4));
        }
        wg_commit();
        wg_wait<0>();
        pin(sacc[0]); pin(sacc[1]); pin(sacc[2]); pin(sacc[3]);
        if (has_mask) {
            uint32_t mf[16];
            const uint32_t lv = lane16 + z32, gg = lv >> 6;
            const uint4* mp = reinterpret_cast<const uint4*>(maskb + (size_t)win * 8192 + ((8 * (gg >> 1) + 2 * (gg & 1)) * 128 + (lv & 48)));
#pragma unroll
            for (int i = 0; i < 4; i++) {
                uint4 t4 = __ldg(mp + 4 * i);
                mf[4 * i] = t4.x; mf[4 * i + 1] = t4.y; mf[4 * i + 2] = t4.z; mf[4 * i + 3] = t4.w;
            }
#pragma unroll
            for (int t = 0; t < 8; t++) {
                const uint32_t a0 = mf[t & 6], a1 = mf[(t & 6) + 1], b0 = mf[8 + (t & 6)], b1 = mf[9 + (t & 6)];
                __half2 ma = as_h2((t & 1) ? pack_f16_sat(bf_hi(a0) * LOG2E, bf_hi(a1) * LOG2E) : pack_f16_sat(bf_lo(a0) * LOG2E, bf_lo(a1) * LOG2E));
                __half2 mb = as_h2((t & 1) ? pack_f16_sat(bf_hi(b0) * LOG2E, bf_hi(b1) * LOG2E) : pack_f16_sat(bf_lo(b0) * LOG2E, bf_lo(b1) * LOG2E));
#pragma unroll
                for (int h = 0; h < 4; h++) {
                    sacc[h][2 * t]     = as_u32(__hadd2(as_h2(sacc[h][2 * t]), ma));
                    sacc[h][2 * t + 1] = as_u32(__hadd2(as_h2(sacc[h][2 * t + 1]), mb));
                }
            }
        }

        if (ACQ == 2) ACQ_TOK;
        TL(7);
        __half2 mx[4];
#pragma unroll
        for (int h = 0; h < 4; h++) {
            const uint32_t* s = sacc[h];
            __half2 ma = as_h2(s[0]), mb = as_h2(s[1]);
#pragma unroll
            for (int t = 1; t < 8; t++) { ma = __hmax2(ma, as_h2(s[2 * t])); mb = __hmax2(mb, as_h2(s[2 * t + 1])); }
            mx[h] = __hmax2(__lows2half2(ma, mb), __highs2half2(ma, mb));
        }
        uint32_t my[4];
#pragma unroll
        for (int h = 0; h < 4; h++) my[h] = __shfl_xor_sync(0xffffffffu, as_u32(mx[h]), 1);
        bar_sync(1 + wg, 128);
        {
            const char* mp = maskb + (size_t)(more ? nwin : 0) * 8192 + lane16;
#pragma unroll
            for (int i = 0; i < 4; i++) ldg_stream(&mr[4 * i], mp + 1024 * i);
        }
#pragma unroll
        for (int h = 0; h < 4; h++) {
            mx[h] = __hmax2(mx[h], as_h2(my[h]));
            my[h] = __shfl_xor_sync(0xffffffffu, as_u32(mx[h]), 2);
        }
        if (more && elect_one()) issue_x(&tmx, nwin, w, kreg + w * XTILE, mbar);
        if (ACQ == 1) ACQ_TOK;
#pragma unroll
        for (int h = 0; h < 4; h++)
            mx[h] = __hadd2(__hmax2(mx[h], as_h2(my[h])), as_h2(0x44004400u));
#pragma unroll
        for (int h = 0; h < 4; h++) {
            __half2 mA = __low2half2(mx[h]), mB = __high2half2(mx[h]);
#pragma unroll
            for (int t = 0; t < 8; t++) {
                sacc[h][2 * t]     = as_u32(__hsub2(as_h2(sacc[h][2 * t]), mA));
                sacc[h][2 * t + 1] = as_u32(__hsub2(as_h2(sacc[h][2 * t + 1]), mB));
            }
        }
        pin(sacc[0]); pin(sacc[1]); pin(sacc[2]); pin(sacc[3]);
        if (ACQ == 0) ACQ_TOK;
        TL(1);
        uint32_t of[24];
        uint32_t o[4][8];
        const uint64_t dv = dv0 + zero;
        STAGE_BEGIN
#pragma unroll
        for (int h = 0; h < 4; h++)
#pragma unroll
            for (int i = 0; i < 16; i++) sacc[h][i] = ex2_h2(sacc[h][i]);
        STAGE_END(0)
        if (REL == 0) REL_TOK;
        wg_fence();
#pragma unroll
        for (int h = 0; h < 4; h++) {
            mma_pv<true>(o[h], &sacc[h][0], dv + (uint64_t)((h * V_HEAD) >> 4));
#pragma unroll
            for (int ks = 1; ks < 4; ks++) mma_pv<false>(o[h], &sacc[h][4 * ks], dv + (uint64_t)((h * V_HEAD + ks * 256) >> 4));
            if (h & 1) wg_commit();
        }
        if (REL == 1) REL_TOK;
#pragma unroll
        for (int h = 0; h < 4; h++) {
            if (h == 0) wg_wait<1>();
            if (h == 2) { wg_wait<0>(); if (REL == 2) REL_TOK; }
            pin(o[h]);
            __half2 inv = as_h2(pack_f16(rcp_fast(__low2float(as_h2(o[h][6]))), rcp_fast(__low2float(as_h2(o[h][7])))));
            __half2 iA = __low2half2(inv), iB = __high2half2(inv);
#pragma unroll
            for (int j = 0; j < 3; j++) {
                of[6 * h + 2 * j]     = as_u32(__hmul2(as_h2(o[h][2 * j]), iA));
                of[6 * h + 2 * j + 1] = as_u32(__hmul2(as_h2(o[h][2 * j + 1]), iB));
            }
        }
        TL(8);
        float acc[48];
        gemm96<false>(acc, of, dwo0 + zero, 2 * WO_LBO);
        char* op;
        {
            int x4, y;
            quadrant_xy(win, w, x4, y);
            const uint32_t lv = lane16 + z32, gg = lv >> 6;
            op = reinterpret_cast<char*>(prm.out) + (uint32_t)((y * IMG + 4 * x4) * 192) + (((gg >> 1) * IMG + 2 * (gg & 1)) * 192 + (lv & 48));
        }
        win = nwin;
        {
            uint32_t any = of[23] & 0x80008000u;
#pragma unroll
            for (int i = 0; i < 8; i++) asm volatile("lop3.b32 %0, %0, %1, %2, 0xFE;" : "+r"(any) : "r"(mr[2 * i]), "r"(mr[2 * i + 1]));
            has_mask = __any_sync(0xffffffffu, (any & 0x7FFF7FFFu) != 0);
        }
        if (more) mbar_wait(mbar, ((n >> 2) & 1) ^ 1);
#pragma unroll
        for (int s = 0; s < 6; s++) ldsm4(&xr[4 * s], xt + (swz(lin_x(lane16 + z32) + 64 * (s >> 1)) ^ (32 * (s & 1))));
#pragma unroll
        for (int i = 0; i < 24; i++) xr[i] = bf2h(xr[i]);
        wg_wait<0>();
        pin(acc);
        wg_fence();
        proj96(ak, xr, dw, 2 * WQKV_LBO);
        bar_sync(1 + wg, 128);
        float a0 = 0.f, a1 = 0.f, b0 = 0.f, b1 = 0.f;
        STAGE_BEGIN
#pragma unroll
            for (int t = 0; t < 12; t++) {
                a0 = fmaf(acc[4 * t], acc[4 * t], a0);         a1 = fmaf(acc[4 * t + 1], acc[4 * t + 1], a1);
                b0 = fmaf(acc[4 * t + 2], acc[4 * t + 2], b0); b1 = fmaf(acc[4 * t + 3], acc[4 * t + 3], b1);
            }
            a0 += a1; b0 += b1;
            a0 += __shfl_xor_sync(0xffffffffu, a0, 1); b0 += __shfl_xor_sync(0xffffffffu, b0, 1);
            a0 += __shfl_xor_sync(0xffffffffu, a0, 2); b0 += __shfl_xor_sync(0xffffffffu, b0, 2);
            float ra = rsqrt_fast(fmaf(a0, 1.0f / 96.0f, 1e-5f)), rb = rsqrt_fast(fmaf(b0, 1.0f / 96.0f, 1e-5f));
#pragma unroll
            for (int j = 0; j < 3; j++) {
                const float* a = &acc[16 * j];
                uint4 va = make_uint4(pack_bf16(a[0] * ra, a[1] * ra), pack_bf16(a[4] * ra, a[5] * ra),
                                      pack_bf16(a[8] * ra, a[9] * ra), pack_bf16(a[12] * ra, a[13] * ra));
                uint4 vb = make_uint4(pack_bf16(a[2] * rb, a[3] * rb), pack_bf16(a[6] * rb, a[7] * rb),
                                      pack_bf16(a[10] * rb, a[11] * rb), pack_bf16(a[14] * rb, a[15] * rb));
                *reinterpret_cast<uint4*>(op + 64 * j) = va;
                *reinterpret_cast<uint4*>(op + 192 + 64 * j) = vb;
            }
        STAGE_END(1)
        wg_wait<0>();
        pin(ak);
        TL(9);
        if (!more) break;
    }
    TL_GT(1);
    TL_DUMP;
}

typedef CUresult (*EncodeTiledFn)(CUtensorMap*, CUtensorMapDataType, cuuint32_t, void*, const cuuint64_t*, const cuuint64_t*,
                                  const cuuint32_t*, const cuuint32_t*, CUtensorMapInterleave, CUtensorMapSwizzle,
                                  CUtensorMapL2promotion, CUtensorMapFloatOOBfill);

}

extern "C" void kernel_launch(void* const* d_in, const int* in_sizes, int n_in, void* d_out, int out_size) {
    (void)in_sizes; (void)n_in; (void)out_size;
    static int sms = 0;
    static EncodeTiledFn encode = nullptr;
    if (sms == 0) {
        int dev = 0;
        cudaGetDevice(&dev);
        cudaDeviceGetAttribute(&sms, cudaDevAttrMultiProcessorCount, dev);
        cudaFuncSetAttribute(swin_attn_kernel, cudaFuncAttributeMaxDynamicSharedMemorySize, SMEM_BYTES + TL_EXTRA);
        void* fn = nullptr;
        cudaDriverEntryPointQueryResult qres;
        cudaGetDriverEntryPoint("cuTensorMapEncodeTiled", &fn, cudaEnableDefault, &qres);
        encode = (EncodeTiledFn)fn;
    }
    CUtensorMap tmx;
    cuuint32_t estr[3]    = {1, 1, 1};
    cuuint64_t dims[3]    = {64, 576, IMG};
    cuuint64_t strides[2] = {128, (cuuint64_t)IMG * 192};
    cuuint32_t box[3]     = {64, 6, 4};
    encode(&tmx, CU_TENSOR_MAP_DATA_TYPE_BFLOAT16, 3, d_in[0], dims, strides, box, estr, CU_TENSOR_MAP_INTERLEAVE_NONE,
           CU_TENSOR_MAP_SWIZZLE_128B, CU_TENSOR_MAP_L2_PROMOTION_NONE, CU_TENSOR_MAP_FLOAT_OOB_FILL_NONE);
    Params prm;
    prm.wqkv = (const __nv_bfloat16*)d_in[1];        prm.wo = (const __nv_bfloat16*)d_in[2];
    prm.logit_scale = (const __nv_bfloat16*)d_in[3]; prm.cpb_w1 = (const __nv_bfloat16*)d_in[4];
    prm.cpb_w2 = (const __nv_bfloat16*)d_in[5];      prm.rel_coords = (const __nv_bfloat16*)d_in[6];
    prm.rel_idx = (const int*)d_in[7];               prm.mask = (const __nv_bfloat16*)d_in[8];
    prm.out = (__nv_bfloat16*)d_out;
    prm.nblk = sms;
    prm.nfull = NWIN / sms;
    prm.rem = NWIN % sms;
    prm.rot = sms >= 32 ? ROT : 0;
    prm.last_rot = (prm.rot * prm.nfull) % sms;
    swin_attn_kernel<<<sms, NTHREADS, SMEM_BYTES + TL_EXTRA>>>(prm, tmx);
}
```

```cpp
#include <cuda.h>
#include <cuda_runtime.h>
#include <cuda_bf16.h>
#include <cuda_fp16.h>
#include <stdint.h>

namespace {

constexpr int NWG      = 4;
constexpr int NTHREADS = NWG * 128;
constexpr int IMG      = 384;
constexpr int WSIDE    = 48;
constexpr int NWIN     = WSIDE * WSIDE;
constexpr int NTAB     = 225;
constexpr float LOG2E  = 1.4426950408889634f;
constexpr float SS_MIN = 1.0f / 512.0f, SS_MAX = 60000.0f;

constexpr int OFF_ZLO  = 0;
constexpr int OFF_WQKV = 1024;
constexpr int WQKV_LBO = 36 * 128;
constexpr int OFF_WO   = OFF_WQKV + 12 * WQKV_LBO;
constexpr int WO_LBO   = 12 * 128;
constexpr int OFF_BIAS = OFF_WO + 12 * WO_LBO;
constexpr int V_HEAD   = 4 * 1024;
constexpr int K_HEAD   = 3 * 1024 + 32;
constexpr int V_STRIDE = 4 * V_HEAD;
constexpr int XTILE    = 3072;
constexpr int K_STRIDE = 13 * 1024;
constexpr int OFF_K    = OFF_BIAS + 32768;
constexpr int OFF_V    = OFF_K + NWG * K_STRIDE;
constexpr int OFF_ZHI  = OFF_V + NWG * V_STRIDE;
constexpr int OFF_SUM  = OFF_ZHI + 1024;
constexpr int OFF_TAB  = OFF_SUM + 256;
constexpr int OFF_MBAR = OFF_TAB + 1808;
constexpr int OFF_TOK  = OFF_MBAR + 176;
constexpr int OFF_QS   = OFF_TOK + 128;
constexpr int SMEM_BYTES = OFF_QS + 16;
constexpr int OFF_PAR  = OFF_V + 55296;
static_assert(OFF_K % 1024 == 0 && OFF_V % 128 == 0 && V_STRIDE % 128 == 0 && OFF_WO % 128 == 0 && OFF_BIAS % 128 == 0, "alignment");
static_assert(4 * K_HEAD <= K_STRIDE && 55296 + 1280 <= NWG * V_STRIDE && OFF_MBAR % 8 == 0, "layout");
static_assert(SMEM_BYTES <= 232448, "smem");

__device__ __forceinline__ uint64_t make_desc(uint32_t addr, uint32_t lbo, uint32_t sbo) {
    return (uint64_t)((addr >> 4) | ((lbo >> 4) << 16)) | ((uint64_t)(sbo >> 4) << 32);
}

__device__ __forceinline__ void wg_fence()  { asm volatile("wgmma.fence.sync.aligned;" ::: "memory"); }
__device__ __forceinline__ void wg_commit() { asm volatile("wgmma.commit_group.sync.aligned;" ::: "memory"); }
template <int N> __device__ __forceinline__ void wg_wait() {
    asm volatile("wgmma.wait_group.sync.aligned %0;" ::"n"(N) : "memory");
}
template <int N> __device__ __forceinline__ void pin(float (&d)[N]) {
#pragma unroll
    for (int i = 0; i < N; i++) asm volatile("" : "+f"(d[i])::"memory");
}
template <int N> __device__ __forceinline__ void pin(uint32_t (&d)[N]) {
#pragma unroll
    for (int i = 0; i < N; i++) asm volatile("" : "+r"(d[i])::"memory");
}

#define F8(C, d, o) C(d[o + 0]), C(d[o + 1]), C(d[o + 2]), C(d[o + 3]), C(d[o + 4]), C(d[o + 5]), C(d[o + 6]), C(d[o + 7])
#define RW_F(x) "+f"(x)
#define WO_F(x) "=f"(x)
#define RW_R(x) "+r"(x)
#define WO_R(x) "=r"(x)

#define N96_REGS                                                                                  \
    "{%0,%1,%2,%3,%4,%5,%6,%7,%8,%9,%10,%11,%12,%13,%14,%15,%16,%17,%18,%19,%20,%21,%22,%23,"     \
    "%24,%25,%26,%27,%28,%29,%30,%31,%32,%33,%34,%35,%36,%37,%38,%39,%40,%41,%42,%43,%44,%45,%46,%47}"

#define MMA_N96(SD, C)                                                                                               \
    asm volatile("wgmma.mma_async.sync.aligned.m64n96k16.f32.f16.f16 " N96_REGS ", {%48,%49,%50,%51}, %52, " SD ", 1, 1, 1;" \
                 : F8(C, d, 0), F8(C, d, 8), F8(C, d, 16), F8(C, d, 24), F8(C, d, 32), F8(C, d, 40)                  \
                 : "r"(a[4 * s]), "r"(a[4 * s + 1]), "r"(a[4 * s + 2]), "r"(a[4 * s + 3]), "l"(db + (uint64_t)(s * (kstep >> 4))))
__device__ __forceinline__ void gemm96(float (&d)[48], const uint32_t (&a)[24], uint64_t db, uint32_t kstep) {
    wg_fence();
#pragma unroll
    for (int s = 0; s < 6; s++) { if (s == 0) MMA_N96("0", WO_F); else MMA_N96("1", RW_F); }
    wg_commit();
}
#define N24_REGS "{%0,%1,%2,%3,%4,%5,%6,%7,%8,%9,%10,%11,%12,%13,%14,%15,%16,%17,%18,%19,%20,%21,%22,%23}"
#define MMA_H96(SD, C)                                                                                               \
    asm volatile("wgmma.mma_async.sync.aligned.m64n96k16.f16.f16.f16 " N24_REGS ", {%24,%25,%26,%27}, %28, " SD ", 1, 1, 1;" \
                 : F8(C, d, 0), F8(C, d, 8), F8(C, d, 16)                                                            \
                 : "r"(a[4 * s]), "r"(a[4 * s + 1]), "r"(a[4 * s + 2]), "r"(a[4 * s + 3]), "l"(db + (uint64_t)(s * (kstep >> 4))))
__device__ __forceinline__ void proj96(uint32_t (&d)[24], const uint32_t (&a)[24], uint64_t db, uint32_t kstep) {
#pragma unroll
    for (int s = 0; s < 6; s++) { if (s == 0) MMA_H96("0", WO_R); else MMA_H96("1", RW_R); }
    wg_commit();
}
#define N16_REGS "{%0,%1,%2,%3,%4,%5,%6,%7,%8,%9,%10,%11,%12,%13,%14,%15}"
__device__ __forceinline__ void mma_qk(uint32_t (&d)[16], const uint32_t* a, uint64_t db) {
    asm volatile("wgmma.mma_async.sync.aligned.m64n64k16.f16.f16.f16 " N16_REGS
                 ", {%16,%17,%18,%19}, %20, 1, 1, 1, 0;"
                 : F8(RW_R, d, 0), F8(RW_R, d, 8)
                 : "r"(a[0]), "r"(a[1]), "r"(a[2]), "r"(a[3]), "l"(db));
}
template <bool FIRST>
__device__ __forceinline__ void mma_pv(uint32_t (&d)[8], const uint32_t* a, uint64_t db) {
    if (FIRST) {
        asm volatile("wgmma.mma_async.sync.aligned.m64n32k16.f16.f16.f16 {%0,%1,%2,%3,%4,%5,%6,%7}, {%8,%9,%10,%11}, %12, 0, 1, 1, 1;"
                     : F8(WO_R, d, 0) : "r"(a[0]), "r"(a[1]), "r"(a[2]), "r"(a[3]), "l"(db));
    } else {
        asm volatile("wgmma.mma_async.sync.aligned.m64n32k16.f16.f16.f16 {%0,%1,%2,%3,%4,%5,%6,%7}, {%8,%9,%10,%11}, %12, 1, 1, 1, 1;"
                     : F8(RW_R, d, 0) : "r"(a[0]), "r"(a[1]), "r"(a[2]), "r"(a[3]), "l"(db));
    }
}

__device__ __forceinline__ void mma_sum(float (&d)[4], const uint32_t* a, uint64_t db) {
    asm volatile("wgmma.mma_async.sync.aligned.m64n8k16.f32.f16.f16 {%0,%1,%2,%3}, {%4,%5,%6,%7}, %8, 0, 1, 1, 0;"
                 : "=f"(d[0]), "=f"(d[1]), "=f"(d[2]), "=f"(d[3]) : "r"(a[0]), "r"(a[1]), "r"(a[2]), "r"(a[3]), "l"(db));
}

__device__ __forceinline__ uint32_t pack_f16(float lo, float hi) {
    uint32_t r; asm("cvt.rn.f16x2.f32 %0, %1, %2;" : "=r"(r) : "f"(hi), "f"(lo)); return r;
}
__device__ __forceinline__ uint32_t pack_f16_sat(float lo, float hi) {
    uint32_t r; asm("cvt.rn.satfinite.f16x2.f32 %0, %1, %2;" : "=r"(r) : "f"(hi), "f"(lo)); return r;
}
__device__ __forceinline__ uint32_t pack_bf16(float lo, float hi) {
    uint32_t r; asm("cvt.rn.bf16x2.f32 %0, %1, %2;" : "=r"(r) : "f"(hi), "f"(lo)); return r;
}
__device__ __forceinline__ float bf_lo(uint32_t v) { return __uint_as_float(v << 16); }
__device__ __forceinline__ float bf_hi(uint32_t v) { return __uint_as_float(v & 0xFFFF0000u); }
__device__ __forceinline__ float bf_round(float x) { return bf_lo(pack_bf16(x, 0.f)); }
__device__ __forceinline__ __half2 as_h2(uint32_t v) { return *reinterpret_cast<__half2*>(&v); }
__device__ __forceinline__ uint32_t as_u32(__half2 v) { return *reinterpret_cast<uint32_t*>(&v); }
__device__ __forceinline__ uint32_t ex2_h2(uint32_t v) {
    uint32_t r; asm("ex2.approx.f16x2 %0, %1;" : "=r"(r) : "r"(v)); return r;
}
__device__ __forceinline__ uint32_t bf2h(uint32_t v) { return pack_f16_sat(bf_lo(v), bf_hi(v)); }
#define HM(x, r) as_u32(__hmul2(as_h2(x), r))
__device__ __forceinline__ float rsqrt_fast(float x) {
    float r; asm("rsqrt.approx.ftz.f32 %0, %1;" : "=f"(r) : "f"(x)); return r;
}
__device__ __forceinline__ float ex2_fast(float x) {
    float r; asm("ex2.approx.ftz.f32 %0, %1;" : "=f"(r) : "f"(x)); return r;
}
__device__ __forceinline__ float rcp_fast(float x) {
    float r; asm("rcp.approx.ftz.f32 %0, %1;" : "=f"(r) : "f"(x)); return r;
}
__device__ __forceinline__ void ldg_stream(uint32_t* r, const void* p) {
    asm volatile("ld.global.L1::no_allocate.v4.u32 {%0,%1,%2,%3}, [%4];"
                 : "=r"(r[0]), "=r"(r[1]), "=r"(r[2]), "=r"(r[3]) : "l"(p) : "memory");
}
__device__ __forceinline__ uint32_t ldg_const32(const void* p) {
    uint32_t r; asm volatile("ld.global.nc.u32 %0, [%1];" : "=r"(r) : "l"(p)); return r;
}
__device__ __forceinline__ void sts128(uint32_t addr, uint32_t a, uint32_t b, uint32_t c, uint32_t d) {
    asm volatile("st.shared.v4.u32 [%0], {%1,%2,%3,%4};" ::"r"(addr), "r"(a), "r"(b), "r"(c), "r"(d) : "memory");
}
__device__ __forceinline__ void lds128(uint32_t* r, uint32_t addr) {
    asm volatile("ld.shared.v4.u32 {%0,%1,%2,%3}, [%4];" : "=r"(r[0]), "=r"(r[1]), "=r"(r[2]), "=r"(r[3]) : "r"(addr));
}
__device__ __forceinline__ void bar_sync(int id, int n)   { asm volatile("bar.sync %0, %1;" ::"r"(id), "r"(n) : "memory"); }
__device__ __forceinline__ void fence_async() { asm volatile("fence.proxy.async.shared::cta;" ::: "memory"); }
template <int K>
__device__ __forceinline__ bool again(int nonneg) {
    uint32_t r;
    asm volatile("{ .reg .pred p; setp.eq.s32 p, %1, %2; selp.u32 %0, 1, 0, p; }" : "=r"(r) : "r"(nonneg), "n"(-1 - K) : "memory");
    return r != 0;
}
#define STAGE_BEGIN _Pragma("unroll 1") do {
#define STAGE_END(k) } while (again<k>(n));
__device__ __forceinline__ void stsm4(uint32_t addr, const uint32_t* r) {
    asm volatile("stmatrix.sync.aligned.m8n8.x4.shared.b16 [%0], {%1,%2,%3,%4};"
                 ::"r"(addr), "r"(r[0]), "r"(r[1]), "r"(r[2]), "r"(r[3]) : "memory");
}
__device__ __forceinline__ void ldsm4(uint32_t* r, uint32_t addr) {
    asm volatile("ldmatrix.sync.aligned.m8n8.x4.shared.b16 {%0,%1,%2,%3}, [%4];"
                 : "=r"(r[0]), "=r"(r[1]), "=r"(r[2]), "=r"(r[3]) : "r"(addr) : "memory");
}
__device__ __forceinline__ void mbar_init(uint32_t mbar, uint32_t count) {
    asm volatile("mbarrier.init.shared::cta.b64 [%0], %1;" ::"r"(mbar), "r"(count) : "memory");
}
__device__ __forceinline__ void mbar_expect(uint32_t mbar, uint32_t bytes) {
    asm volatile("mbarrier.arrive.expect_tx.shared::cta.b64 _, [%0], %1;" ::"r"(mbar), "r"(bytes) : "memory");
}
__device__ __forceinline__ void mbar_wait(uint32_t mbar, uint32_t parity) {
    uint32_t ok;
    int spins = 0;
    do {
        asm volatile("{ .reg .pred p; mbarrier.try_wait.parity.shared::cta.b64 p, [%1], %2; selp.u32 %0, 1, 0, p; }"
                     : "=r"(ok) : "r"(mbar), "r"(parity) : "memory");
    } while (!ok && ++spins < (1 << 22));
}
__device__ __forceinline__ bool elect_one() {
    uint32_t p;
    asm volatile("{ .reg .pred p; elect.sync _|p, 0xffffffff; selp.u32 %0, 1, 0, p; }" : "=r"(p));
    return p != 0;
}
__device__ __forceinline__ void warp_arrive(uint32_t mbar) {
    __syncwarp();
    if (elect_one()) asm volatile("mbarrier.arrive.shared::cta.b64 _, [%0];" ::"r"(mbar) : "memory");
}
__device__ __forceinline__ void bulk_copy(uint32_t dst, const void* src, uint32_t bytes, uint32_t mbar) {
    asm volatile("cp.async.bulk.shared::cluster.global.mbarrier::complete_tx::bytes [%0], [%1], %2, [%3];"
                 ::"r"(dst), "l"(src), "r"(bytes), "r"(mbar) : "memory");
}
__device__ __forceinline__ void quadrant_xy(int win, int w, int& x4, int& y) {
    int wy = win / WSIDE, wx = win - wy * WSIDE;
    y  = wy * 8 + 4 + 4 * (w >> 1);
    x4 = wx * 2 + 1 + (w & 1);
    if (y >= IMG) y -= IMG;
    if (x4 >= IMG / 4) x4 -= IMG / 4;
}
__device__ __forceinline__ void issue_x(const CUtensorMap* tm, int win, int w, uint32_t dst, uint32_t mbar) {
    int x4, y;
    quadrant_xy(win, w, x4, y);
    mbar_expect(mbar, XTILE);
    asm volatile("cp.async.bulk.tensor.3d.shared::cluster.global.mbarrier::complete_tx::bytes [%0], [%1, {%2, %3, %4}], [%5];"
                 ::"r"(dst), "l"(tm), "r"(0), "r"(6 * x4), "r"(y), "r"(mbar) : "memory");
}
__device__ __forceinline__ int wrap(int p, int n) { return p >= n ? p - n : p; }
__device__ __forceinline__ uint32_t swz(uint32_t lin) { return lin ^ ((lin >> 3) & 0x70); }
__device__ __forceinline__ uint32_t lin_x(uint32_t l16) { return (l16 & 112) * 24 + ((l16 >> 7) & 1) * 192 + ((l16 >> 4) & 16); }

__device__ __forceinline__ void layernorm_store(const float (&acc)[48], char* op, float (&z)[4]) {
    float &a0 = z[0], &a1 = z[1], &b0 = z[2], &b1 = z[3];
#pragma unroll
    for (int t = 0; t < 12; t++) {
        a0 = fmaf(acc[4 * t], acc[4 * t], a0);         a1 = fmaf(acc[4 * t + 1], acc[4 * t + 1], a1);
        b0 = fmaf(acc[4 * t + 2], acc[4 * t + 2], b0); b1 = fmaf(acc[4 * t + 3], acc[4 * t + 3], b1);
    }
    a0 += a1; b0 += b1;
    a0 += __shfl_xor_sync(0xffffffffu, a0, 1); b0 += __shfl_xor_sync(0xffffffffu, b0, 1);
    a0 += __shfl_xor_sync(0xffffffffu, a0, 2); b0 += __shfl_xor_sync(0xffffffffu, b0, 2);
    float ra = rsqrt_fast(fmaf(a0, 1.0f / 96.0f, 1e-5f)), rb = rsqrt_fast(fmaf(b0, 1.0f / 96.0f, 1e-5f));
#pragma unroll
    for (int j = 0; j < 3; j++) {
        const float* a = &acc[16 * j];
        uint4 va = make_uint4(pack_bf16(a[0] * ra, a[1] * ra), pack_bf16(a[4] * ra, a[5] * ra),
                              pack_bf16(a[8] * ra, a[9] * ra), pack_bf16(a[12] * ra, a[13] * ra));
        uint4 vb = make_uint4(pack_bf16(a[2] * rb, a[3] * rb), pack_bf16(a[6] * rb, a[7] * rb),
                              pack_bf16(a[10] * rb, a[11] * rb), pack_bf16(a[14] * rb, a[15] * rb));
        *reinterpret_cast<uint4*>(op + 64 * j) = va;
        *reinterpret_cast<uint4*>(op + 192 + 64 * j) = vb;
    }
}

__device__ __forceinline__ void row_max(const uint32_t (&s)[16], __half2& m) {
    __half2 ma = as_h2(s[0]), mb = as_h2(s[1]);
#pragma unroll
    for (int t = 1; t < 8; t++) { ma = __hmax2(ma, as_h2(s[2 * t])); mb = __hmax2(mb, as_h2(s[2 * t + 1])); }
    m = __hmax2(__lows2half2(ma, mb), __highs2half2(ma, mb));
}
__device__ __forceinline__ int window_id(int n, int nblk, int pos) { return NWIN - 1 - (n * nblk + pos); }

struct Params {
    const __nv_bfloat16 *wqkv, *cpb_w1, *cpb_w2, *rel_coords, *wo, *logit_scale, *mask;
    const int* rel_idx;
    __nv_bfloat16* out;
    int nblk, nfull, last_rot, rem, rot;
};

__global__ void __launch_bounds__(NTHREADS, 1)
swin_attn_kernel(const Params prm, const __grid_constant__ CUtensorMap tmx) {
    extern __shared__ __align__(1024) uint8_t smem[];
    const uint32_t sbase = (uint32_t)__cvta_generic_to_shared(smem);
    const int tid  = threadIdx.x;
    const int wi = __shfl_sync(0xffffffffu, tid >> 5, 0);
    const uint32_t mbar_w = sbase + OFF_MBAR + 128, mbar_p = mbar_w + 16, mbar_o = mbar_w + 24;
    const uint32_t mbar_r = mbar_w + 32, mbar_b = mbar_w + 8, mbar_c = mbar_w + 40;
    if (wi == 0 && elect_one()) {
        mbar_init(mbar_w, 1);
        mbar_init(mbar_p, 1);
        mbar_init(mbar_o, 1);
        fence_async();
        mbar_expect(mbar_p, 64 + 128 + 896);
        mbar_expect(mbar_w, 55296);
        bulk_copy(sbase + OFF_PAR, prm.cpb_w1, 64, mbar_p);
        bulk_copy(sbase + OFF_PAR + 128, prm.cpb_w2, 128, mbar_p);
        bulk_copy(sbase + OFF_PAR + 256, prm.rel_coords, 896, mbar_p);
        bulk_copy(sbase + OFF_V, prm.wqkv, 55296, mbar_w);
        mbar_expect(mbar_o, 16384 + 18432);
        bulk_copy(sbase + OFF_BIAS, prm.rel_idx, 16384, mbar_o);
        bulk_copy(sbase + OFF_WO, prm.wo, 18432, mbar_o);
    }
    const int lane = tid & 31;
    const int g = lane >> 2, c = lane & 3;
    const int wg = wi >> 2, w = wi & 3;
    const uint32_t mbar = sbase + OFF_MBAR + 8 * wi;
    if (elect_one()) {
        mbar_init(mbar, 1);
        mbar_init(sbase + OFF_TOK + 8 * wi, 1);
        if (wi == 1) asm volatile("prefetch.tensormap [%0];" ::"l"(&tmx) : "memory");
        if (wi == 4) {
            mbar_init(mbar_b, 8);
            mbar_init(mbar_c, 8);
            mbar_init(mbar_r, 16);
        }
        fence_async();
    }
    const int nblk = prm.nblk;
    const int cnt = prm.nfull + (wrap(blockIdx.x + prm.last_rot, nblk) < prm.rem ? 1 : 0);
    int n = wg;
    int pos = wrap(blockIdx.x + prm.rot * wg, nblk);
    const char* maskb = reinterpret_cast<const char*>(prm.mask) + (32 * (w >> 1) + 4 * (w & 1)) * 128;
    const uint32_t vreg = sbase + OFF_V + wg * V_STRIDE;
    const uint32_t kreg = sbase + OFF_K + wg * K_STRIDE;
    const uint32_t lane16 = lane * 16;
    int win = max(window_id(n, nblk, pos), 0);
    __syncthreads();
    uint32_t mr[16];
    const int ent = tid - 256;
    if (wg < 2) {
        if (wg == 0) {
            if (elect_one()) issue_x(&tmx, win, w, kreg + w * XTILE, mbar);
            __syncwarp();
#pragma unroll
            for (int i = 0; i < 4; i++) ldg_stream(&mr[4 * i], maskb + (size_t)win * 8192 + lane16 + 1024 * i);
        } else {
            sts128(sbase + (w < 2 ? OFF_ZLO : OFF_ZHI - 1024) + (tid - 128) * 16, 0u, 0u, 0u, 0u);
            if (tid < 128 + 16) {
                const uint32_t one = ((tid ^ (tid >> 3)) & 1) ? 0u : 0x3C003C00u;
                sts128(sbase + OFF_SUM + lane16, one, one, one, one);
            }
        }
    } else {
        uint32_t small = 0;
        if (wi == 15) small = ldg_const32(lane < 16 ? reinterpret_cast<const uint32_t*>(prm.rel_coords) + NTAB - 1
                                                    : reinterpret_cast<const uint32_t*>(prm.logit_scale) + (c >> 1));
        mbar_wait(mbar_p, 0);
        uint32_t w1[16], w2[32];
#pragma unroll
        for (int i = 0; i < 4; i++) lds128(&w1[4 * i], sbase + OFF_PAR + 16 * i);
#pragma unroll
        for (int i = 0; i < 8; i++) lds128(&w2[4 * i], sbase + OFF_PAR + 128 + 16 * i);
        const uint32_t rc = ent >= NTAB - 1 ? small : *reinterpret_cast<const uint32_t*>(smem + OFF_PAR + 256 + 4 * ent);
        float r0 = bf_lo(rc), r1 = bf_hi(rc), z[4] = {0.f, 0.f, 0.f, 0.f};
#pragma unroll
        for (int j = 0; j < 16; j += 2) {
            uint32_t hp = pack_bf16(fmaf(r1, bf_lo(w1[8 + (j >> 1)]), r0 * bf_lo(w1[j >> 1])),
                                    fmaf(r1, bf_hi(w1[8 + (j >> 1)]), r0 * bf_hi(w1[j >> 1])));
            float h0 = bf_lo(hp), h1 = bf_hi(hp);
            h0 = h0 > 0.f ? h0 : h0 * 0.f;
            h1 = h1 > 0.f ? h1 : h1 * 0.f;
            z[0] = fmaf(h0, bf_lo(w2[2 * j]), z[0]);     z[1] = fmaf(h0, bf_hi(w2[2 * j]), z[1]);
            z[2] = fmaf(h0, bf_lo(w2[2 * j + 1]), z[2]); z[3] = fmaf(h0, bf_hi(w2[2 * j + 1]), z[3]);
            z[0] = fmaf(h1, bf_lo(w2[2 * j + 2]), z[0]); z[1] = fmaf(h1, bf_hi(w2[2 * j + 2]), z[1]);
            z[2] = fmaf(h1, bf_lo(w2[2 * j + 3]), z[2]); z[3] = fmaf(h1, bf_hi(w2[2 * j + 3]), z[3]);
        }
#pragma unroll
        for (int h = 0; h < 4; h++) z[h] = bf_round(rcp_fast(1.0f + ex2_fast(-LOG2E * bf_round(z[h])))) * (16.0f * LOG2E);
        if (ent < NTAB)
            asm volatile("st.shared.v2.u32 [%0], {%1,%2};" ::"r"(sbase + OFF_TAB + ent * 8), "r"(pack_f16(z[0], z[1])),
                         "r"(pack_f16(z[2], z[3])) : "memory");
        if (tid >= NTHREADS - 4) {
            float ls = bf_round(fminf(fmaxf((c & 1) ? bf_hi(small) : bf_lo(small), -100.0f), 4.6052f));
            float qs = bf_round(ex2_fast(ls * LOG2E)) * LOG2E;
            asm volatile("st.shared.f32 [%0], %1;" ::"r"(sbase + OFF_QS + c * 4), "f"(qs) : "memory");
        }
    }
    {
        const int k8 = tid & 7, rot = k8 >> 1;
        uint32_t src[2], dst[2];
        {
            int rest = tid >> 3;
            int pj = rest / 12, kg = rest - 12 * pj;
            src[0] = sbase + OFF_V + (kg * 8 + k8) * 576 + (pj < 3 ? 384 + 64 * pj : 64 * pj - 192);
            dst[0] = sbase + OFF_WQKV + kg * WQKV_LBO + (12 + 4 * pj) * 128 + k8 * 16;
            if (wi < 9) {
                int j = pj + (rot == 3 ? 0 : rot);
                j -= j >= 3 ? 3 : 0;
                src[1] = sbase + OFF_V + (kg * 8 + k8) * 576 + 192 + 16 * j;
                dst[1] = sbase + OFF_WQKV + kg * WQKV_LBO + 4 * j * 128 + k8 * 16;
            } else {
                kg = rest - 32;
                src[1] = sbase + OFF_V + (kg * 8 + k8) * 576 + 128;
                dst[1] = sbase + OFF_WQKV + kg * WQKV_LBO + 32 * 128 + k8 * 16;
            }
        }
        mbar_wait(mbar_w, 0);
        uint32_t v[2][4][4];
#pragma unroll
        for (int q = 0; q < 4; q++) lds128(v[0][q], src[0] + 16 * ((q + rot) & 3));
        if (wi < 11) {
#pragma unroll
            for (int q = 0; q < 4; q++) lds128(v[1][q], src[1] + (wi < 9 ? 48 * q : 16 * ((q + rot) & 3)));
        }
        if (wg == 1) {
            if (elect_one()) issue_x(&tmx, win, w, kreg + w * XTILE, mbar);
            __syncwarp();
#pragma unroll
            for (int i = 0; i < 4; i++) ldg_stream(&mr[4 * i], maskb + (size_t)win * 8192 + lane16 + 1024 * i);
        }
#pragma unroll
        for (int q = 0; q < 4; q++)
            sts128(dst[0] + 128 * ((q + rot) & 3), bf2h(v[0][q][0]), bf2h(v[0][q][1]), bf2h(v[0][q][2]), bf2h(v[0][q][3]));
        if (wi < 9) {
#pragma unroll
            for (int q = 0; q < 4; q++) sts128(dst[1] + 128 * q, bf2h(v[1][0][q]), bf2h(v[1][1][q]), bf2h(v[1][2][q]), bf2h(v[1][3][q]));
        } else if (wi < 11) {
#pragma unroll
            for (int q = 0; q < 4; q++)
                sts128(dst[1] + 128 * ((q + rot) & 3), bf2h(v[1][q][0]), bf2h(v[1][q][1]), bf2h(v[1][q][2]), bf2h(v[1][q][3]));
        }
        fence_async();
        warp_arrive(mbar_r);
    }
    if (wg >= 2) {
        uint32_t wov[2][12];
        int4 ri[2][2];
        const int bq = w ^ (g & 1);
        mbar_wait(mbar_o, 0);
#pragma unroll
        for (int r = 0; r < 2; r++)
#pragma unroll
            for (int j = 0; j < 3; j++) lds128(&wov[r][4 * j], sbase + OFF_WO + min(64 * r + (ent >> 2), 95) * 192 + 64 * j + 16 * c);
#pragma unroll
        for (int i = 0; i < 2; i++) {
            const int bw = wg - 2 + 2 * i;
            const uint32_t p = sbase + OFF_BIAS + ((32 * (bw >> 1) + 4 * (bw & 1) + 8 * (g >> 1) + 2 * (g & 1)) * 64 + 32 * (w >> 1) + 8 * c + 4 * (bq & 1)) * 4;
            lds128(reinterpret_cast<uint32_t*>(&ri[i][0]), p);
            lds128(reinterpret_cast<uint32_t*>(&ri[i][1]), p + 256);
        }
        if (n < cnt && elect_one()) issue_x(&tmx, win, w, kreg + w * XTILE, mbar);
        __syncwarp();
#pragma unroll
        for (int i = 0; i < 4; i++) ldg_stream(&mr[4 * i], maskb + (size_t)win * 8192 + lane16 + 1024 * i);
        bar_sync(9, 256);
#pragma unroll
        for (int i = 0; i < 2; i++) {
            const int4 ra = ri[i][0], rb = ri[i][1];
            int id[8] = {ra.x, ra.z, rb.x, rb.z, ra.y, ra.w, rb.y, rb.w};
            uint2 e[8];
#pragma unroll
            for (int k = 0; k < 8; k++)
                e[k] = *reinterpret_cast<const uint2*>(smem + OFF_TAB + min((unsigned)id[k], (unsigned)(NTAB - 1)) * 8);
            uint32_t dst = sbase + OFF_BIAS + ((wg - 2 + 2 * i) * 4 + bq) * 512 + lane16;
            sts128(dst,         __byte_perm(e[0].x, e[1].x, 0x5410), __byte_perm(e[2].x, e[3].x, 0x5410),
                                __byte_perm(e[4].x, e[5].x, 0x5410), __byte_perm(e[6].x, e[7].x, 0x5410));
            sts128(dst + 8192,  __byte_perm(e[0].x, e[1].x, 0x7632), __byte_perm(e[2].x, e[3].x, 0x7632),
                                __byte_perm(e[4].x, e[5].x, 0x7632), __byte_perm(e[6].x, e[7].x, 0x7632));
            sts128(dst + 16384, __byte_perm(e[0].y, e[1].y, 0x5410), __byte_perm(e[2].y, e[3].y, 0x5410),
                                __byte_perm(e[4].y, e[5].y, 0x5410), __byte_perm(e[6].y, e[7].y, 0x5410));
            sts128(dst + 24576, __byte_perm(e[0].y, e[1].y, 0x7632), __byte_perm(e[2].y, e[3].y, 0x7632),
                                __byte_perm(e[4].y, e[5].y, 0x7632), __byte_perm(e[6].y, e[7].y, 0x7632));
        }
        warp_arrive(mbar_b);
#pragma unroll
        for (int r = 0; r < 2; r++) {
            const int krow = 64 * r + (ent >> 2);
            float s = 0.f;
#pragma unroll
            for (int i = 0; i < 12; i++) s += bf_lo(wov[r][i]) + bf_hi(wov[r][i]);
            s += __shfl_xor_sync(0xffffffffu, s, 1);
            s += __shfl_xor_sync(0xffffffffu, s, 2);
            const float mean = s * (1.0f / 96.0f);
            const uint32_t dst = sbase + OFF_WO + (krow >> 3) * WO_LBO + (krow & 7) * 16 + 4 * c;
            if (krow < 96) {
#pragma unroll
                for (int i = 0; i < 12; i++) {
                    uint32_t p = pack_f16_sat(bf_lo(wov[r][i]) - mean, bf_hi(wov[r][i]) - mean);
                    asm volatile("st.shared.u32 [%0], %1;" ::"r"(dst + i * 128), "r"(p) : "memory");
                }
            }
        }
        fence_async();
        warp_arrive(mbar_c);
    }

    const uint32_t st_k = kreg + c * K_HEAD + (16 * w + g) * 16;
    const uint32_t xt = kreg + w * XTILE;
    const uint32_t ubias = sbase + OFF_BIAS + w * 2048;
    const uint64_t dw0  = make_desc(sbase + OFF_WQKV, WQKV_LBO, 128);
    const uint64_t dwo0 = make_desc(sbase + OFF_WO, WO_LBO, 128);
    const uint64_t dk0  = make_desc(kreg, 1024, 128);
    const uint64_t dkh0 = make_desc(kreg + 2048, sbase + OFF_ZHI - (kreg + 2048), 128);
    const uint64_t dkl0 = make_desc(sbase + OFF_ZLO, kreg + K_HEAD - (sbase + OFF_ZLO), 128);
    const uint64_t dv0  = make_desc(vreg, 128, 1024);
    const uint64_t dsum0 = make_desc(sbase + OFF_SUM, 128, 128);

    if (n >= cnt) return;
    uint32_t xr[24], ak[24];
    mbar_wait(mbar, 0);
#pragma unroll
    for (int s = 0; s < 6; s++) ldsm4(&xr[4 * s], xt + (swz(lin_x(lane16) + 64 * (s >> 1)) ^ (32 * (s & 1))));
#pragma unroll
    for (int i = 0; i < 24; i++) xr[i] = bf2h(xr[i]);
    mbar_wait(mbar_r, 0);
    const float tau = *reinterpret_cast<const float*>(smem + OFF_QS + c * 4);
    wg_fence();
    proj96(ak, xr, dw0, 2 * WQKV_LBO);
#pragma unroll
    for (int i = 0; i < 2; i++) {
        int idx = (tid & 127) + 128 * i;
        sts128(vreg + (idx >> 6) * V_HEAD + 3 * 1024 + (idx & 63) * 16, 0x3C003C00u, 0x3C003C00u, 0x3C003C00u, 0x3C003C00u);
    }
    bar_sync(1 + wg, 128);
    wg_wait<0>();
    pin(ak);
    bool has_mask;
    {
        uint32_t any = ak[23] & 0x80008000u;
#pragma unroll
        for (int i = 0; i < 8; i++) asm volatile("lop3.b32 %0, %0, %1, %2, 0xFE;" : "+r"(any) : "r"(mr[2 * i]), "r"(mr[2 * i + 1]));
        has_mask = __any_sync(0xffffffffu, (any & 0x7FFF7FFFu) != 0);
    }

    float acc[48];
    char* op;
    for (;; n += NWG) {
        pos = wrap(pos + NWG * prm.rot, nblk);
        const int nwin = window_id(n + NWG, nblk, pos);
        const bool more = n + NWG < cnt;
        const uint32_t z32 = n >> 30;
        const uint64_t zero = z32;
        const uint64_t dw = dw0 + zero;
        uint32_t av[24], qf[24];
        wg_fence();
        proj96(av, xr, dw + ((12 * 128) >> 4), 2 * WQKV_LBO);
        {
            __half2 sa = __hmul2(as_h2(ak[0]), as_h2(ak[0])), sb = __hmul2(as_h2(ak[1]), as_h2(ak[1]));
            __half2 ta = __hmul2(as_h2(ak[2]), as_h2(ak[2])), tb = __hmul2(as_h2(ak[3]), as_h2(ak[3]));
#pragma unroll
            for (int t = 2; t < 12; t += 2) {
                sa = __hfma2(as_h2(ak[2 * t]), as_h2(ak[2 * t]), sa);         sb = __hfma2(as_h2(ak[2 * t + 1]), as_h2(ak[2 * t + 1]), sb);
                ta = __hfma2(as_h2(ak[2 * t + 2]), as_h2(ak[2 * t + 2]), ta); tb = __hfma2(as_h2(ak[2 * t + 3]), as_h2(ak[2 * t + 3]), tb);
            }
            sa = __hadd2(sa, ta); sb = __hadd2(sb, tb);
            float fa = __low2float(sa) + __high2float(sa), fb = __low2float(sb) + __high2float(sb);
            __half2 r = as_h2(pack_f16_sat(rsqrt_fast(fa) * tau, rsqrt_fast(fb) * tau));
            if (__any_sync(0xffffffffu, !(fminf(fa, fb) >= SS_MIN && fa + fb < SS_MAX))) {
                fa = 1e-12f; fb = 1e-12f;
#pragma unroll
                for (int t = 0; t < 12; t++) {
                    float2 u = __half22float2(as_h2(ak[2 * t])), v = __half22float2(as_h2(ak[2 * t + 1]));
                    fa = fmaf(u.x, u.x, fmaf(u.y, u.y, fa)); fb = fmaf(v.x, v.x, fmaf(v.y, v.y, fb));
                }
                fa = rsqrt_fast(fa) * tau; fb = rsqrt_fast(fb) * tau;
#pragma unroll
                for (int t = 0; t < 12; t++) {
                    float2 u = __half22float2(as_h2(ak[2 * t])), v = __half22float2(as_h2(ak[2 * t + 1]));
                    ak[2 * t] = pack_f16(u.x * fa, u.y * fa); ak[2 * t + 1] = pack_f16(v.x * fb, v.y * fb);
                }
                r = as_h2(0x3C003C00u);
            }
            __half2 ra = __low2half2(r), rb = __high2half2(r);
#pragma unroll
            for (int j = 0; j < 3; j++) {
                const uint32_t* a = &ak[8 * j];
                sts128(st_k + j * 1024, HM(a[0], ra), HM(a[2], ra), HM(a[4], ra), HM(a[6], ra));
                sts128(st_k + j * 1024 + 128, HM(a[1], rb), HM(a[3], rb), HM(a[5], rb), HM(a[7], rb));
            }
        }
        wg_fence();
        proj96(qf, xr, dw + ((24 * 128) >> 4), 2 * WQKV_LBO);
        wg_wait<1>();
        pin(av);
#pragma unroll
        for (int p = 0; p < 6; p++) {
            const int t0 = 2 * p;
            const uint32_t hi = (lane16 + z32) & 256;
            stsm4(lane16 + (t0 % 3 == 2 ? 7 : 3) * hi + (vreg + 256 * w + (t0 / 3) * V_HEAD + (t0 % 3) * 1024), &av[4 * p]);
        }
        if (has_mask) {
            const uint32_t lv = lane16 + z32;
            asm volatile("prefetch.global.L1 [%0];" ::"l"(maskb + (size_t)win * 8192 + ((lv & 192) * 16 + (lv & 48) * 8)));
        }
        if (n < NWG) mbar_wait(mbar_b, 0);
        uint32_t sacc[4][16];
        wg_wait<0>();
        pin(qf);
        {
            uint32_t ps[8];
            float ss[2][4];
#pragma unroll
            for (int h = 0; h < 4; h++) {
                const uint32_t* a = &qf[6 * h];
                __half2 sa = __hmul2(as_h2(a[0]), as_h2(a[0])), sb = __hmul2(as_h2(a[1]), as_h2(a[1]));
                sa = __hfma2(as_h2(a[2]), as_h2(a[2]), sa); sb = __hfma2(as_h2(a[3]), as_h2(a[3]), sb);
                ps[2 * h] = as_u32(__hfma2(as_h2(a[4]), as_h2(a[4]), sa)); ps[2 * h + 1] = as_u32(__hfma2(as_h2(a[5]), as_h2(a[5]), sb));
            }
            wg_fence();
            mma_sum(ss[0], &ps[0], dsum0 + zero);
            mma_sum(ss[1], &ps[4], dsum0 + zero);
            wg_commit();
#pragma unroll
            for (int h = 0; h < 2; h++)
#pragma unroll
                for (int q = 0; q < 4; q++) lds128(&sacc[h][4 * q], lane16 + ubias + h * 8192 + q * 512);
            fence_async();
            bar_sync(1 + wg, 128);
            wg_wait<0>();
            pin(ss[0]); pin(ss[1]);
            __half2 rq[4];
#pragma unroll
            for (int h = 0; h < 4; h++) rq[h] = as_h2(pack_f16_sat(rsqrt_fast(ss[h >> 1][h & 1]), rsqrt_fast(ss[h >> 1][2 + (h & 1)])));
#pragma unroll
            for (int h = 2; h < 4; h++)
#pragma unroll
                for (int q = 0; q < 4; q++) lds128(&sacc[h][4 * q], lane16 + ubias + h * 8192 + q * 512);
            const __half2 rmin = __hmin2_nan(__hmin2_nan(rq[0], rq[1]), __hmin2_nan(rq[2], rq[3]));
            const __half2 rmax = __hmax2(__hmax2(rq[0], rq[1]), __hmax2(rq[2], rq[3]));
            if (__any_sync(0xffffffffu, !(__hbgt2(rmin, __float2half2_rn(0.0041f)) && __hble2(rmax, __float2half2_rn(22.6f))))) {
#pragma unroll
                for (int h = 0; h < 4; h++) {
                    float fa = 0.25e-12f, fb = 0.25e-12f;
#pragma unroll
                    for (int j = 0; j < 3; j++) {
                        float2 u = __half22float2(as_h2(qf[6 * h + 2 * j])), v = __half22float2(as_h2(qf[6 * h + 2 * j + 1]));
                        fa = fmaf(u.x, u.x, fmaf(u.y, u.y, fa)); fb = fmaf(v.x, v.x, fmaf(v.y, v.y, fb));
                    }
                    fa += __shfl_xor_sync(0xffffffffu, fa, 1); fb += __shfl_xor_sync(0xffffffffu, fb, 1);
                    fa += __shfl_xor_sync(0xffffffffu, fa, 2); fb += __shfl_xor_sync(0xffffffffu, fb, 2);
                    fa = rsqrt_fast(fa); fb = rsqrt_fast(fb);
#pragma unroll
                    for (int j = 0; j < 3; j++) {
                        float2 u = __half22float2(as_h2(qf[6 * h + 2 * j])), v = __half22float2(as_h2(qf[6 * h + 2 * j + 1]));
                        qf[6 * h + 2 * j] = pack_f16(u.x * fa, u.y * fa); qf[6 * h + 2 * j + 1] = pack_f16(v.x * fb, v.y * fb);
                    }
                    rq[h] = as_h2(0x3C003C00u);
                }
            }
#pragma unroll
            for (int h = 0; h < 4; h++) {
                __half2 ra = __low2half2(rq[h]), rb = __high2half2(rq[h]);
#pragma unroll
                for (int j = 0; j < 3; j++) {
                    qf[6 * h + 2 * j]     = HM(qf[6 * h + 2 * j], ra);
                    qf[6 * h + 2 * j + 1] = HM(qf[6 * h + 2 * j + 1], rb);
                }
            }
        }
        wg_fence();
        {
            const uint64_t dk = dk0 + zero, dkh = dkh0 + zero, dkl = dkl0 + zero;
            constexpr uint64_t HP = (2 * K_HEAD) >> 4;
            mma_qk(sacc[0], &qf[0], dk);
            mma_qk(sacc[1], &qf[4], dkl);
            mma_qk(sacc[0], &qf[4], dkh);
            mma_qk(sacc[1], &qf[8], dk + ((K_HEAD + 1024) >> 4));
            wg_commit();
            mma_qk(sacc[2], &qf[12], dk + HP);
            mma_qk(sacc[3], &qf[16], dkl + (HP << 16));
            mma_qk(sacc[2], &qf[16], dkh + HP - (HP << 16));
            mma_qk(sacc[3], &qf[20], dk + HP + ((K_HEAD + 1024) >> 4));
        }
        wg_commit();
        __half2 mx[4];
        wg_wait<1>();
        pin(sacc[0]); pin(sacc[1]);
        row_max(sacc[0], mx[0]); row_max(sacc[1], mx[1]);
        wg_wait<0>();
        pin(sacc[2]); pin(sacc[3]);
        row_max(sacc[2], mx[2]); row_max(sacc[3], mx[3]);
        if (has_mask) {
            uint32_t mf[16];
            const uint32_t lv = lane16 + z32, gg = lv >> 6;
            const uint4* mp = reinterpret_cast<const uint4*>(maskb + (size_t)win * 8192 + ((8 * (gg >> 1) + 2 * (gg & 1)) * 128 + (lv & 48)));
#pragma unroll
            for (int i = 0; i < 4; i++) {
                uint4 t4 = __ldg(mp + 4 * i);
                mf[4 * i] = t4.x; mf[4 * i + 1] = t4.y; mf[4 * i + 2] = t4.z; mf[4 * i + 3] = t4.w;
            }
#pragma unroll
            for (int t = 0; t < 8; t++) {
                const uint32_t a0 = mf[t & 6], a1 = mf[(t & 6) + 1], b0 = mf[8 + (t & 6)], b1 = mf[9 + (t & 6)];
                __half2 ma = as_h2((t & 1) ? pack_f16_sat(bf_hi(a0) * LOG2E, bf_hi(a1) * LOG2E) : pack_f16_sat(bf_lo(a0) * LOG2E, bf_lo(a1) * LOG2E));
                __half2 mb = as_h2((t & 1) ? pack_f16_sat(bf_hi(b0) * LOG2E, bf_hi(b1) * LOG2E) : pack_f16_sat(bf_lo(b0) * LOG2E, bf_lo(b1) * LOG2E));
#pragma unroll
                for (int h = 0; h < 4; h++) {
                    sacc[h][2 * t]     = as_u32(__hadd2(as_h2(sacc[h][2 * t]), ma));
                    sacc[h][2 * t + 1] = as_u32(__hadd2(as_h2(sacc[h][2 * t + 1]), mb));
                }
            }
#pragma unroll
            for (int h = 0; h < 4; h++) row_max(sacc[h], mx[h]);
        }

        uint32_t my[4];
#pragma unroll
        for (int h = 0; h < 4; h++) my[h] = __shfl_xor_sync(0xffffffffu, as_u32(mx[h]), 1);
        bar_sync(1 + wg, 128);
        {
            const char* mp = maskb + (size_t)(more ? nwin : 0) * 8192 + lane16;
#pragma unroll
            for (int i = 0; i < 4; i++) ldg_stream(&mr[4 * i], mp + 1024 * i);
        }
#pragma unroll
        for (int h = 0; h < 4; h++) {
            mx[h] = __hmax2(mx[h], as_h2(my[h]));
            my[h] = __shfl_xor_sync(0xffffffffu, as_u32(mx[h]), 2);
        }
        if (more && elect_one()) issue_x(&tmx, nwin, w, kreg + w * XTILE, mbar);
        mbar_wait(n > 0 ? sbase + OFF_TOK + 8 * wi : mbar_c, n > 0 ? ((n - 1) >> 2) & 1 : 0);
#pragma unroll
        for (int h = 0; h < 4; h++)
            mx[h] = __hadd2(__hmax2(mx[h], as_h2(my[h])), as_h2(0x44004400u));
        uint32_t of[24];
        uint32_t o[4][8];
        const uint64_t dv = dv0 + zero;
        STAGE_BEGIN
#pragma unroll
        for (int h = 0; h < 4; h++) {
            const __half2 mA = __low2half2(mx[h]), mB = __high2half2(mx[h]);
#pragma unroll
            for (int t = 0; t < 8; t++) {
                sacc[h][2 * t]     = ex2_h2(as_u32(__hsub2(as_h2(sacc[h][2 * t]), mA)));
                sacc[h][2 * t + 1] = ex2_h2(as_u32(__hsub2(as_h2(sacc[h][2 * t + 1]), mB)));
            }
        }
        STAGE_END(0)
        warp_arrive(sbase + OFF_TOK + 8 * ((wi + 4) & 15));
        wg_fence();
#pragma unroll
        for (int hp = 0; hp < 4; hp += 2) {
#pragma unroll
            for (int ks = 0; ks < 4; ks++)
#pragma unroll
                for (int h = hp; h < hp + 2; h++) {
                    if (ks == 0) mma_pv<true>(o[h], &sacc[h][0], dv + (uint64_t)((h * V_HEAD) >> 4));
                    else         mma_pv<false>(o[h], &sacc[h][4 * ks], dv + (uint64_t)((h * V_HEAD + ks * 256) >> 4));
                }
            wg_commit();
        }
#pragma unroll
        for (int h = 0; h < 4; h++) {
            if (h == 0) wg_wait<1>();
            if (h == 2) wg_wait<0>();
            pin(o[h]);
            __half2 inv = as_h2(pack_f16(rcp_fast(__low2float(as_h2(o[h][6]))), rcp_fast(__low2float(as_h2(o[h][7])))));
            __half2 iA = __low2half2(inv), iB = __high2half2(inv);
#pragma unroll
            for (int j = 0; j < 3; j++) {
                of[6 * h + 2 * j]     = as_u32(__hmul2(as_h2(o[h][2 * j]), iA));
                of[6 * h + 2 * j + 1] = as_u32(__hmul2(as_h2(o[h][2 * j + 1]), iB));
            }
        }
        gemm96(acc, of, dwo0 + zero, 2 * WO_LBO);
        {
            int x4, y;
            quadrant_xy(win, w, x4, y);
            const uint32_t lv = lane16 + z32, gg = lv >> 6;
            op = reinterpret_cast<char*>(prm.out) + (uint32_t)((y * IMG + 4 * x4) * 192) + (((gg >> 1) * IMG + 2 * (gg & 1)) * 192 + (lv & 48));
        }
        if (!more) break;
        win = nwin;
        {
            uint32_t any = of[23] & 0x80008000u;
#pragma unroll
            for (int i = 0; i < 8; i++) asm volatile("lop3.b32 %0, %0, %1, %2, 0xFE;" : "+r"(any) : "r"(mr[2 * i]), "r"(mr[2 * i + 1]));
            has_mask = __any_sync(0xffffffffu, (any & 0x7FFF7FFFu) != 0);
        }
        mbar_wait(mbar, ((n >> 2) & 1) ^ 1);
#pragma unroll
        for (int s = 0; s < 6; s++) ldsm4(&xr[4 * s], xt + (swz(lin_x(lane16 + z32) + 64 * (s >> 1)) ^ (32 * (s & 1))));
        STAGE_BEGIN
#pragma unroll
        for (int i = 0; i < 24; i++) xr[i] = bf2h(xr[i]);
        STAGE_END(2)
        wg_wait<0>();
        pin(acc);
        wg_fence();
        proj96(ak, xr, dw, 2 * WQKV_LBO);
        bar_sync(1 + wg, 128);
        float z[4] = {0.f, 0.f, 0.f, 0.f};
        STAGE_BEGIN
        layernorm_store(acc, op, z);
        STAGE_END(1)
        wg_wait<0>();
        pin(ak);
    }
    wg_wait<0>();
    pin(acc);
    {
        float z[4] = {0.f, 0.f, 0.f, 0.f};
        layernorm_store(acc, op, z);
    }
}

typedef CUresult (*EncodeTiledFn)(CUtensorMap*, CUtensorMapDataType, cuuint32_t, void*, const cuuint64_t*, const cuuint64_t*,
                                  const cuuint32_t*, const cuuint32_t*, CUtensorMapInterleave, CUtensorMapSwizzle,
                                  CUtensorMapL2promotion, CUtensorMapFloatOOBfill);

}

extern "C" void kernel_launch(void* const* d_in, const int* in_sizes, int n_in, void* d_out, int out_size) {
    (void)in_sizes; (void)n_in; (void)out_size;
    static int sms = 0;
    static EncodeTiledFn encode = nullptr;
    if (sms == 0) {
        int dev = 0;
        cudaGetDevice(&dev);
        cudaDeviceGetAttribute(&sms, cudaDevAttrMultiProcessorCount, dev);
        if (sms > NWIN / NWG) sms = NWIN / NWG;
        cudaFuncSetAttribute(swin_attn_kernel, cudaFuncAttributeMaxDynamicSharedMemorySize, SMEM_BYTES);
        void* fn = nullptr;
        cudaDriverEntryPointQueryResult qres;
        cudaGetDriverEntryPoint("cuTensorMapEncodeTiled", &fn, cudaEnableDefault, &qres);
        encode = (EncodeTiledFn)fn;
    }
    CUtensorMap tmx;
    cuuint32_t estr[3]    = {1, 1, 1};
    cuuint64_t dims[3]    = {64, 576, IMG};
    cuuint64_t strides[2] = {128, (cuuint64_t)IMG * 192};
    cuuint32_t box[3]     = {64, 6, 4};
    encode(&tmx, CU_TENSOR_MAP_DATA_TYPE_BFLOAT16, 3, d_in[0], dims, strides, box, estr, CU_TENSOR_MAP_INTERLEAVE_NONE,
           CU_TENSOR_MAP_SWIZZLE_128B, CU_TENSOR_MAP_L2_PROMOTION_NONE, CU_TENSOR_MAP_FLOAT_OOB_FILL_NONE);
    Params prm;
    prm.wqkv = (const __nv_bfloat16*)d_in[1];        prm.wo = (const __nv_bfloat16*)d_in[2];
    prm.logit_scale = (const __nv_bfloat16*)d_in[3]; prm.cpb_w1 = (const __nv_bfloat16*)d_in[4];
    prm.cpb_w2 = (const __nv_bfloat16*)d_in[5];      prm.rel_coords = (const __nv_bfloat16*)d_in[6];
    prm.rel_idx = (const int*)d_in[7];               prm.mask = (const __nv_bfloat16*)d_in[8];
    prm.out = (__nv_bfloat16*)d_out;
    prm.nblk = sms;
    prm.nfull = NWIN / sms;
    prm.rem = NWIN % sms;
    prm.rot = sms >= 32 ? 5 : 0;
    prm.last_rot = (prm.rot * prm.nfull) % sms;
    swin_attn_kernel<<<sms, NTHREADS, SMEM_BYTES>>>(prm, tmx);
}
```
